```python
import torch

def _softmax(x, axis=-1):
    return torch.softmax(x, dim=axis)
def _gelu(x):
    return torch.nn.functional.gelu(x, approximate="tanh")
def _silu(x):
    return torch.nn.functional.silu(x)
def _sigmoid(x):
    return torch.sigmoid(x)
def _layernorm(x, axis=-1, eps=1e-5):
    m = x.mean(dim=axis, keepdim=True)
    v = x.var(dim=axis, keepdim=True, unbiased=False)
    return (x - m) / torch.sqrt(v + eps)
def _scatter_add(tgt, idx, src, axis=0):
    return tgt.clone().index_add_(axis, idx, src)
def _segment_sum(src, seg, n):
    out = torch.zeros((n,) + src.shape[1:], dtype=src.dtype)
    return out.index_add_(0, seg, src)
def _pad(x, pw):
    flat = tuple(v for pair in reversed(pw) for v in pair)
    return torch.nn.functional.pad(x, flat)

kernel_name = 'standalone__edge_featured_mpnn_egc__graph'

def setup_inputs():

    _w = (lambda a: (lambda t: t.to(torch.bfloat16) if t.is_floating_point() else t)(torch.as_tensor(a)))
    N, deg, D, De = 10000, 16, 256, max(16, 1)
    E = N * deg
    return {
        "x": _w((lambda *s: torch.randn(*s, dtype=torch.bfloat16) * 0.1)(N, D)),
        "e_attr": _w((lambda *s: torch.randn(*s, dtype=torch.bfloat16) * 0.1)(E, De)),
        "src": _w((lambda lo, hi, *s: torch.randint(lo, hi, s))(0, N, E).to(torch.int64)),
        "dst": _w((lambda lo, hi, *s: torch.randint(lo, hi, s))(0, N, E).to(torch.int64)),
        "u_w": _w((lambda *s: torch.randn(*s, dtype=torch.bfloat16) * 0.05)(D, D)),
        "v_w": _w((lambda *s: torch.randn(*s, dtype=torch.bfloat16) * 0.05)(D, D)),
        "g_w": _w((lambda *s: torch.randn(*s, dtype=torch.bfloat16) * 0.1)(2 * D + De, D)),
    }

def reference(x, e_attr, src, dst, u_w, v_w, g_w):
    N, D = x.shape
    g_in = torch.concatenate([x[dst], x[src], e_attr], axis=-1)
    eta = _sigmoid(g_in @ g_w)
    hv = x @ v_w
    msg = eta * hv[src]
    agg = _segment_sum(msg, dst, N)
    return _silu(x @ u_w + agg)
```

```cpp
#include <cuda_runtime.h>
#include <cuda_bf16.h>
#include <cuda.h>
#include <stdint.h>

namespace {

constexpr int D = 256;
constexpr int DE = 16;
constexpr int NPAD_MAX = 12288;
constexpr int MAXG = 160;
constexpr int GMAX = 132;
constexpr int PAIR = 32;
constexpr int NPAIR = 152;
constexpr int NPC_MAX = 76;
constexpr int MAXNG = 5;

#define GP0 0
#define NWARP2 7
constexpr int NCONS = 8;
constexpr int NW2 = NWARP2;
constexpr int NTHREADS = (NCONS + 1 + NW2) * 32;
#define NPRODW 2
constexpr int NPROD = NPRODW;
constexpr int NBIN = NTHREADS - 32;
constexpr int EPT = (1248 + NBIN - 1) / NBIN;
constexpr int NB2 = NW2 * 32;

constexpr int XKB = NPAIR * 128;
constexpr int SM_X = 0;
constexpr int NWS = 7;
constexpr int SM_W = SM_X + 4 * XKB;
constexpr int SM_S = SM_W + NWS * 8192;
constexpr int SBLK = NPC_MAX * 128;
constexpr int SHALF = 4 * SBLK;
constexpr int SM_REC = SM_S + 8 * SBLK;
constexpr int REC_SLOTS = 1760;
constexpr int SM_ROFF = SM_REC;
constexpr int SM_RMETA = SM_REC + 4 * REC_SLOTS;
constexpr int SM_BAR = SM_REC + 8 * REC_SLOTS;
constexpr int ROWB = 1024;
constexpr int METAO = 16 * ROWB;
constexpr int STAGEB = 16 * ROWB + 16 * 64;
#define NSTAGES 7
constexpr int NST = NSTAGES;
constexpr int OUTW = 16 * 80;
constexpr int SM_OUT = NST * STAGEB;
static_assert(SM_OUT + NCONS * OUTW <= SM_S, "smem overlap");
constexpr int SC_STG = 0;
constexpr int SC_HIST = SC_STG + GMAX * PAIR * 8;
static_assert(SC_HIST + 4 * MAXG <= SHALF, "binning scratch too large");
constexpr int BAR_FULL = SM_BAR;
constexpr int BAR_EMPTY = BAR_FULL + 8 * NST;
constexpr int BAR_WF = BAR_EMPTY + 8 * NST;
constexpr int BAR_WE = BAR_WF + 8 * NWS;
constexpr int BAR_XF = BAR_WE + 8 * NWS;
constexpr int BAR_CNT = BAR_XF + 8 * 4;
constexpr int BAR_GO = BAR_CNT + 8;
constexpr int BAR_STF = BAR_GO + 8;
constexpr int BAR_TD = BAR_STF + 16;
constexpr int BAR_PSF = BAR_TD + 8;
constexpr int BAR_SR = BAR_PSF + 8;
constexpr int BAR_GD = BAR_SR + 8;
constexpr int BAR_XE = BAR_GD + 8;
constexpr int SM_CNT = BAR_XE + 8 * 4;
constexpr int SM_SLOT = SM_CNT + 4 * 8;
constexpr int SM_DUMMY = (SM_SLOT + 64 + 127) / 128 * 128;
constexpr int SM_TOTAL = SM_DUMMY + 128;
static_assert(SM_TOTAL % 8 == 0 && SM_TOTAL + 256 <= 232448, "smem too large");

struct Params {
    const __nv_bfloat16* e_attr;
    const int* src;
    const int* dst;
    const __nv_bfloat16* cw;
    __nv_bfloat16* out;
    const char* tabT;
    const char *wG, *wV, *wU;
    int2* inbox;
    unsigned *barA, *barB;
    int N, E;
    int npc, ng, epc, capg;
    unsigned magic;
};

__device__ __nv_bfloat16 g_T[NPAD_MAX * 512];
__device__ int2 g_inbox[MAXG * MAXG * PAIR];
__device__ unsigned g_barA[32];
__device__ unsigned g_barB[32];

#define TL(k) do { } while (0)
#define TLP(k, cond) do { } while (0)
constexpr int SM_ALLOC = SM_TOTAL;

__device__ __forceinline__ void mbar_init(uint32_t bar, uint32_t cnt) {
    asm volatile("mbarrier.init.shared::cta.b64 [%0], %1;" ::"r"(bar), "r"(cnt) : "memory");
}
__device__ __forceinline__ void mbar_expect_tx(uint32_t bar, uint32_t bytes) {
    asm volatile("mbarrier.arrive.expect_tx.shared::cta.b64 _, [%0], %1;" ::"r"(bar), "r"(bytes) : "memory");
}
__device__ __forceinline__ void mbar_arrive(uint32_t bar) {
    asm volatile("mbarrier.arrive.shared::cta.b64 _, [%0];" ::"r"(bar) : "memory");
}
__device__ __forceinline__ void mbar_arrive_if(uint32_t bar, bool pred) {
    asm volatile("{\n.reg .pred p;\nsetp.ne.u32 p, %1, 0;\n@p mbarrier.arrive.shared::cta.b64 _, [%0];\n}" ::"r"(bar), "r"((uint32_t)pred) : "memory");
}
__device__ __forceinline__ bool mbar_test(uint32_t bar, uint32_t parity) {
    uint32_t ok;
    asm volatile("{\n.reg .pred p;\nmbarrier.test_wait.parity.shared::cta.b64 p, [%1], %2;\nselp.u32 %0, 1, 0, p;\n}"
                 : "=r"(ok) : "r"(bar), "r"(parity) : "memory");
    return ok != 0;
}
__device__ __forceinline__ void mbar_wait(uint32_t bar, uint32_t parity) {
    asm volatile(
        "{\n.reg .pred p;\n.reg .u32 n;\n"
        "mbarrier.try_wait.parity.shared::cta.b64 p, [%0], %1;\n"
        "@p bra DONE_%=;\n"
        "mov.u32 n, 0;\n"
        "WAIT_%=:\n"
        "mbarrier.try_wait.parity.shared::cta.b64 p, [%0], %1;\n"
        "@p bra DONE_%=;\n"
        "add.u32 n, n, 1;\n"
        "setp.lt.u32 p, n, 4194304;\n"
        "@p bra WAIT_%=;\n"
        "trap;\n"
        "DONE_%=:\n}"
        ::"r"(bar), "r"(parity) : "memory");
}
__device__ __forceinline__ void tma_load3d(uint32_t dst, const CUtensorMap* tm, int row, int blk, uint32_t bar) {
    asm volatile("cp.async.bulk.tensor.3d.shared::cluster.global.tile.mbarrier::complete_tx::bytes [%0], [%1, {%3, %4, %5}], [%2];"
                 ::"r"(dst), "l"(tm), "r"(bar), "r"(0), "r"(row), "r"(blk) : "memory");
}
__device__ __forceinline__ void tma_store3d(const CUtensorMap* tm, uint32_t src, int row, int blk) {
    asm volatile("cp.async.bulk.tensor.3d.global.shared::cta.tile.bulk_group [%0, {%2, %3, %4}], [%1];"
                 ::"l"(tm), "r"(src), "r"(0), "r"(row), "r"(blk) : "memory");
}
__device__ __forceinline__ uint32_t mapa(uint32_t addr, uint32_t rank) {
    uint32_t r;
    asm("mapa.shared::cluster.u32 %0, %1, %2;" : "=r"(r) : "r"(addr), "r"(rank));
    return r;
}
__device__ __forceinline__ void mbar_wait_cluster(uint32_t bar, uint32_t parity) {
    asm volatile(
        "{\n.reg .pred p;\n.reg .u32 n;\n"
        "mov.u32 n, 0;\n"
        "WAIT_%=:\n"
        "mbarrier.try_wait.parity.acquire.cluster.shared::cta.b64 p, [%0], %1;\n"
        "@p bra DONE_%=;\n"
        "add.u32 n, n, 1;\n"
        "setp.lt.u32 p, n, 4194304;\n"
        "@p bra WAIT_%=;\n"
        "trap;\n"
        "DONE_%=:\n}"
        ::"r"(bar), "r"(parity) : "memory");
}
__device__ __forceinline__ void bar_sync(int id, int n) { asm volatile("bar.sync %0, %1;" ::"r"(id), "r"(n) : "memory"); }
__device__ __forceinline__ void bar_arrive(int id, int n) { asm volatile("bar.arrive %0, %1;" ::"r"(id), "r"(n) : "memory"); }

__device__ __forceinline__ void ldsm4(uint32_t (&r)[4], uint32_t addr) {
    asm volatile("ldmatrix.sync.aligned.m8n8.x4.shared.b16 {%0,%1,%2,%3}, [%4];"
                 : "=r"(r[0]), "=r"(r[1]), "=r"(r[2]), "=r"(r[3]) : "r"(addr));
}
__device__ __forceinline__ void ldsm4t(uint32_t (&r)[4], uint32_t addr) {
    asm volatile("ldmatrix.sync.aligned.m8n8.x4.trans.shared.b16 {%0,%1,%2,%3}, [%4];"
                 : "=r"(r[0]), "=r"(r[1]), "=r"(r[2]), "=r"(r[3]) : "r"(addr));
}
__device__ __forceinline__ void stsm4t(uint32_t addr, uint32_t a, uint32_t b, uint32_t c, uint32_t d) {
    asm volatile("stmatrix.sync.aligned.m8n8.x4.trans.shared.b16 [%0], {%1,%2,%3,%4};"
                 ::"r"(addr), "r"(a), "r"(b), "r"(c), "r"(d) : "memory");
}
__device__ __forceinline__ void stsm2t(uint32_t addr, uint32_t a, uint32_t b) {
    asm volatile("stmatrix.sync.aligned.m8n8.x2.trans.shared.b16 [%0], {%1,%2};" ::"r"(addr), "r"(a), "r"(b) : "memory");
}
__device__ __forceinline__ void mma16(float (&d)[4], const uint32_t (&a)[4], uint32_t b0, uint32_t b1) {
    asm("mma.sync.aligned.m16n8k16.row.col.f32.bf16.bf16.f32 {%0,%1,%2,%3}, {%4,%5,%6,%7}, {%8,%9}, {%0,%1,%2,%3};"
        : "+f"(d[0]), "+f"(d[1]), "+f"(d[2]), "+f"(d[3])
        : "r"(a[0]), "r"(a[1]), "r"(a[2]), "r"(a[3]), "r"(b0), "r"(b1));
}
__device__ __forceinline__ void mma16z(float (&d)[4], const uint32_t (&a)[4], uint32_t b0, uint32_t b1) {
    asm("mma.sync.aligned.m16n8k16.row.col.f32.bf16.bf16.f32 {%0,%1,%2,%3}, {%4,%5,%6,%7}, {%8,%9}, {%10,%10,%10,%10};"
        : "=f"(d[0]), "=f"(d[1]), "=f"(d[2]), "=f"(d[3])
        : "r"(a[0]), "r"(a[1]), "r"(a[2]), "r"(a[3]), "r"(b0), "r"(b1), "f"(0.f));
}
__device__ __forceinline__ void mma8(float (&d)[4], uint32_t a0, uint32_t a1, uint32_t b0) {
    asm("mma.sync.aligned.m16n8k8.row.col.f32.bf16.bf16.f32 {%0,%1,%2,%3}, {%4,%5}, {%6}, {%0,%1,%2,%3};"
        : "+f"(d[0]), "+f"(d[1]), "+f"(d[2]), "+f"(d[3])
        : "r"(a0), "r"(a1), "r"(b0));
}
__device__ __forceinline__ void mma8z(float (&d)[4], uint32_t a0, uint32_t a1, uint32_t b0) {
    asm("mma.sync.aligned.m16n8k8.row.col.f32.bf16.bf16.f32 {%0,%1,%2,%3}, {%4,%5}, {%6}, {%7,%7,%7,%7};"
        : "=f"(d[0]), "=f"(d[1]), "=f"(d[2]), "=f"(d[3])
        : "r"(a0), "r"(a1), "r"(b0), "f"(0.f));
}
__device__ __forceinline__ uint32_t pack_bf16(float lo, float hi) {
    uint32_t r;
    asm("cvt.rn.bf16x2.f32 %0, %1, %2;" : "=r"(r) : "f"(hi), "f"(lo));
    return r;
}
__device__ __forceinline__ float tanh_fast(float x) {
    float r;
    asm("tanh.approx.f32 %0, %1;" : "=f"(r) : "f"(x));
    return r;
}
__device__ __forceinline__ uint32_t fma_bf16x2(uint32_t a, uint32_t b, uint32_t c) {
    uint32_t r;
    asm("fma.rn.bf16x2 %0, %1, %2, %3;" : "=r"(r) : "r"(a), "r"(b), "r"(c));
    return r;
}
__device__ __forceinline__ unsigned ld_acquire(const unsigned* p) {
    unsigned v;
    asm volatile("ld.acquire.gpu.global.u32 %0, [%1];" : "=r"(v) : "l"(p) : "memory");
    return v;
}
__device__ __forceinline__ unsigned grid_arrive(unsigned* bar) {
    unsigned old;
    asm volatile("atom.add.release.gpu.global.u32 %0, [%1], 1;" : "=r"(old) : "l"(bar) : "memory");
    return (old / gridDim.x + 1) * gridDim.x;
}
__device__ __forceinline__ void grid_wait(const unsigned* bar, unsigned target) {
    uint32_t spins = 0;
    while ((int)(ld_acquire(bar) - target) < 0) {
        if (++spins > (1u << 22)) __trap();
    }
}

__device__ __forceinline__ void wgmma_n152(float (&d)[76], uint64_t da, uint64_t db, int scale_d) {
    asm volatile(
        "{\n.reg .pred p;\nsetp.ne.b32 p, %78, 0;\n"
        "wgmma.mma_async.sync.aligned.m64n152k16.f32.bf16.bf16 "
        "{%0,%1,%2,%3,%4,%5,%6,%7,%8,%9,%10,%11,%12,%13,%14,%15,%16,%17,%18,%19,%20,%21,%22,%23,%24,%25,%26,%27,%28,%29,%30,%31,%32,%33,%34,%35,%36,%37,%38,%39,%40,%41,%42,%43,%44,%45,%46,%47,%48,%49,%50,%51,%52,%53,%54,%55,%56,%57,%58,%59,%60,%61,%62,%63,%64,%65,%66,%67,%68,%69,%70,%71,%72,%73,%74,%75}, "
        "%76, %77, p, 1, 1, 1, 0;\n}"
        : "+f"(d[0]), "+f"(d[1]), "+f"(d[2]), "+f"(d[3]), "+f"(d[4]), "+f"(d[5]), "+f"(d[6]), "+f"(d[7]), "+f"(d[8]), "+f"(d[9]), "+f"(d[10]), "+f"(d[11]), "+f"(d[12]), "+f"(d[13]), "+f"(d[14]), "+f"(d[15]), "+f"(d[16]), "+f"(d[17]), "+f"(d[18]), "+f"(d[19]), "+f"(d[20]), "+f"(d[21]), "+f"(d[22]), "+f"(d[23]), "+f"(d[24]), "+f"(d[25]), "+f"(d[26]), "+f"(d[27]), "+f"(d[28]), "+f"(d[29]), "+f"(d[30]), "+f"(d[31]), "+f"(d[32]), "+f"(d[33]), "+f"(d[34]), "+f"(d[35]), "+f"(d[36]), "+f"(d[37]), "+f"(d[38]), "+f"(d[39]), "+f"(d[40]), "+f"(d[41]), "+f"(d[42]), "+f"(d[43]), "+f"(d[44]), "+f"(d[45]), "+f"(d[46]), "+f"(d[47]), "+f"(d[48]), "+f"(d[49]), "+f"(d[50]), "+f"(d[51]), "+f"(d[52]), "+f"(d[53]), "+f"(d[54]), "+f"(d[55]), "+f"(d[56]), "+f"(d[57]), "+f"(d[58]), "+f"(d[59]), "+f"(d[60]), "+f"(d[61]), "+f"(d[62]), "+f"(d[63]), "+f"(d[64]), "+f"(d[65]), "+f"(d[66]), "+f"(d[67]), "+f"(d[68]), "+f"(d[69]), "+f"(d[70]), "+f"(d[71]), "+f"(d[72]), "+f"(d[73]), "+f"(d[74]), "+f"(d[75])
        : "l"(da), "l"(db), "r"(scale_d));
}

__device__ __forceinline__ void cp16(uint32_t dst, const void* src) {
    asm volatile("cp.async.cg.shared.global [%0], [%1], 16;" ::"r"(dst), "l"(src) : "memory");
}
__device__ __forceinline__ void sts128(uint32_t a, uint32_t x, uint32_t y, uint32_t z, uint32_t w) {
    asm volatile("st.shared.v4.u32 [%0], {%1,%2,%3,%4};" ::"r"(a), "r"(x), "r"(y), "r"(z), "r"(w) : "memory");
}
__device__ __forceinline__ uint4 lds128(uint32_t a) {
    uint4 v;
    asm volatile("ld.shared.v4.u32 {%0,%1,%2,%3}, [%4];" : "=r"(v.x), "=r"(v.y), "=r"(v.z), "=r"(v.w) : "r"(a));
    return v;
}
__device__ __forceinline__ void chunk_done(uint32_t fullbar, int lane) {
    asm volatile("cp.async.mbarrier.arrive.noinc.shared::cta.b64 [%0];" ::"r"(fullbar) : "memory");
    __syncwarp();
    if (lane == 0) mbar_arrive(fullbar);
}
__device__ __forceinline__ void copy_row(uint32_t dst, const char* src) {
    cp16(dst, src);
    cp16(dst + 512, src + 512);
}
__device__ __forceinline__ void put_meta(const Params& p, uint32_t stage, uint32_t meta, bool valid, int lane) {
    const int slot = lane >> 1, half = lane & 1;
    const uint32_t a = stage + METAO + slot * 64 + ((half ^ ((slot >> 1) & 3)) << 4);
    uint32_t w0 = 0, w1 = 0, w2 = 0, w3 = 0;
    if (valid) {
        cp16(a, reinterpret_cast<const char*>(p.e_attr) + (size_t)(meta & 0x3FFFF) * (DE * 2) + half * 16);
        const uint32_t dl = meta >> 18;
        const uint32_t v = (dl >> 3) == (uint32_t)half ? 0x3F00u << ((dl & 1) * 16) : 0u;
        const uint32_t wi = (dl >> 1) & 3;
        w0 = wi == 0 ? v : 0; w1 = wi == 1 ? v : 0; w2 = wi == 2 ? v : 0; w3 = wi == 3 ? v : 0;
    } else {
        sts128(a, 0, 0, 0, 0);
    }
    sts128(a ^ 32, w0, w1, w2, w3);
}
__device__ __forceinline__ void issue_partial_chunk(const Params& p, uint32_t stage, uint32_t fullbar, uint32_t roff, uint32_t rmeta,
                                                    int nvalid, int lane) {
    const uint32_t sline = stage + (lane >> 3) * 128;
    for (int k = 0; k < 16; k++) {
        const uint32_t off = __shfl_sync(0xffffffffu, roff, k);
        const uint32_t dst = sline + k * ROWB + (((lane & 7) ^ (k & 7)) << 4);
        if (k < nvalid) {
            copy_row(dst, p.tabT + off + lane * 16);
        } else {
            sts128(dst, 0, 0, 0, 0);
            sts128(dst + 512, 0, 0, 0, 0);
        }
    }
    const uint32_t meta = __shfl_sync(0xffffffffu, rmeta, lane >> 1);
    put_meta(p, stage, meta, (lane >> 1) < nvalid, lane);
    chunk_done(fullbar, lane);
}

struct TrueT { static constexpr bool value = true; };
struct FalseT { static constexpr bool value = false; };

__global__ void __cluster_dims__(2, 1, 1) __launch_bounds__(NTHREADS, 1)
mpnn_fused_kernel(const __grid_constant__ CUtensorMap tmX, const __grid_constant__ CUtensorMap tmG,
                  const __grid_constant__ CUtensorMap tmV, const __grid_constant__ CUtensorMap tmU,
                  const __grid_constant__ CUtensorMap tmT, const Params p) {
    extern __shared__ __align__(1024) unsigned char smem_raw[];
    const uint32_t sb = (uint32_t)__cvta_generic_to_shared(smem_raw);
    const int warp = __shfl_sync(0xffffffffu, threadIdx.x >> 5, 0), lane = threadIdx.x & 31;
    const int c = blockIdx.x, G = gridDim.x;
    const int rank = c & 1;
    const int prow0 = (c >> 1) * 2 * p.npc;
    const int n0 = c * p.npc;
    const int n1 = min(n0 + p.npc, p.N);
    volatile int* s_cnt = reinterpret_cast<volatile int*>(smem_raw + SM_CNT);

    auto load_w = [&](int i, int slot) {
        const int b = i >> 2, kc = i & 3;
        const CUtensorMap* tm = rank == 0 ? &tmG : (b < 4 ? &tmV : &tmU);
        const int row = (b < 4 && rank == 0 ? 256 : 0) + kc * 64;
        mbar_expect_tx(sb + BAR_WF + 8 * slot, 8192);
        tma_load3d(sb + SM_W + slot * 8192, tm, row, b & 3, sb + BAR_WF + 8 * slot);
    };
    const int scr = SM_S + (1 - rank) * SHALF;

    const int tb1 = threadIdx.x < NCONS * 32 ? threadIdx.x : threadIdx.x - 32;
    const int e0 = c * p.epc, e1 = min(e0 + p.epc, p.E);
    int dv[EPT], sv[EPT];
    if (warp != NCONS) {
#pragma unroll
        for (int i = 0; i < EPT; i++) {
            const int e = e0 + i * NBIN + tb1;
            dv[i] = e < e1 ? __ldg(p.dst + e) : -1;
            sv[i] = e < e1 ? __ldg(p.src + e) : 0;
        }
        if (tb1 >= 192 && tb1 < 192 + MAXG) *reinterpret_cast<int*>(smem_raw + scr + SC_HIST + 4 * (tb1 - 192)) = 0;
        if (tb1 >= 160 && tb1 < 168) *reinterpret_cast<int*>(smem_raw + SM_CNT + 4 * (tb1 - 160)) = 0;
    } else if (lane == 0) {
        TL(0);
        for (int i = c; i < 130; i += G) {
            const char* w = i < 66 ? p.wG + i * 4096 : (i < 98 ? p.wV + (i - 66) * 4096 : p.wU + (i - 98) * 4096);
            asm volatile("cp.async.bulk.prefetch.L2.global [%0], %1;" ::"l"(w), "r"(4096) : "memory");
        }
#pragma unroll
        for (int i = 0; i < NWS; i++) mbar_init(sb + BAR_WF + 8 * i, 1);
#pragma unroll
        for (int i = 0; i < 4; i++) mbar_init(sb + BAR_XF + 8 * i, 1);
        asm volatile("fence.mbarrier_init.release.cluster;" ::: "memory");
#pragma unroll
        for (int kc = 0; kc < 4; kc++) {
            mbar_expect_tx(sb + BAR_XF + 8 * kc, XKB);
            tma_load3d(sb + SM_X + kc * XKB, &tmX, prow0, kc, sb + BAR_XF + 8 * kc);
            load_w(kc, kc);
        }
#pragma unroll
        for (int i = 4; i < NWS; i++) load_w(i, i);
#pragma unroll
        for (int i = 0; i < NST; i++) { mbar_init(sb + BAR_FULL + 8 * i, 33); mbar_init(sb + BAR_EMPTY + 8 * i, NCONS); }
#pragma unroll
        for (int i = 0; i < NWS; i++) mbar_init(sb + BAR_WE + 8 * i, 4);
        mbar_init(sb + BAR_CNT, 1);
        mbar_init(sb + BAR_GO, 1);
        mbar_init(sb + BAR_STF, 1);
        mbar_init(sb + BAR_STF + 8, 1);
        mbar_init(sb + BAR_TD, 2);
        mbar_init(sb + BAR_PSF, 1);
        mbar_init(sb + BAR_SR, 1);
        mbar_init(sb + BAR_GD, NCONS);
#pragma unroll
        for (int i = 0; i < 4; i++) mbar_init(sb + BAR_XE + 8 * i, NCONS);
        mbar_expect_tx(sb + BAR_SR, 4 * p.npc * 128);
        asm volatile("fence.mbarrier_init.release.cluster;" ::: "memory");
    }
    __syncthreads();
    asm volatile("barrier.cluster.arrive.relaxed.aligned;" ::: "memory");

    if (warp == NCONS) asm volatile("barrier.cluster.wait.aligned;" ::: "memory");
    if (warp != NCONS) {
        int2* stg = reinterpret_cast<int2*>(smem_raw + scr + SC_STG);
        int* s_hist = reinterpret_cast<int*>(smem_raw + scr + SC_HIST);
        TLP(23, threadIdx.x == 0 && dv[0] != -77);
#pragma unroll
        for (int i = 0; i < EPT; i++) {
            const int o = __umulhi((unsigned)max(dv[i], 0), p.magic);
            const int rank_o = dv[i] >= 0 ? atomicAdd(&s_hist[o], 1) : PAIR;
            if (rank_o < PAIR - 1)
                stg[o * PAIR + 1 + rank_o] = make_int2(sv[i], (e0 + i * NBIN + tb1) | ((dv[i] - o * p.npc) << 18));
        }
        asm volatile("barrier.cluster.wait.aligned;" ::: "memory");
        bar_sync(3, NBIN);
        if (threadIdx.x == 288) TL(22);
        {
            const int k = lane & 15, w = tb1 >> 5;
#pragma unroll
            for (int i = 0; i < (GMAX + NBIN / 16 - 1) / (NBIN / 16); i++) {
                const int o = (NBIN / 16) * i + 2 * w + (lane >> 4);
                if (o < G) {
                    const int tot = s_hist[o];
                    uint4 v = lds128(sb + scr + SC_STG + o * (PAIR * 8) + k * 16);
                    if (k == 0) { v.x = tot; v.y = 0; }
                    if (2 * k <= (min(tot, PAIR - 1) | 3)) *reinterpret_cast<uint4*>(&p.inbox[(o * G + c) * PAIR + 2 * k]) = v;
                }
            }
        }
        TLP(26, threadIdx.x == 0);
        if (warp < NCONS) bar_arrive(3, NBIN); else bar_sync(3, NBIN);
        if (threadIdx.x == 288) TL(27);
    }

    if (warp < NCONS) {
        const int wg = warp >> 2, wj = warp & 3;
        {
            const uint64_t descHi = ((uint64_t)(1024 >> 4) << 32) | (1ull << 62) | (1ull << 16);
            const int stn = (lane & 7) + ((lane >> 4) << 3);
            const int stc = 2 * wj + ((lane >> 3) & 1);
            const uint32_t shalf = sb + SM_S + rank * SHALF;
            const uint32_t peer_sb = mapa(sb, rank ^ 1);
            int slot = 4 * wg, wphase = 0;
            for (int b = wg; b < 8; b += 2) {
                float acc[76];
                uint32_t sl[4], par[4];
#pragma unroll
                for (int kc = 0; kc < 4; kc++) {
                    const int t = slot + kc;
                    sl[kc] = t >= NWS ? t - NWS : t;
                    par[kc] = wphase ^ (t >= NWS);
                }
                const uint64_t db = descHi | (uint64_t)(((sb + SM_X) & 0x3FFFF) >> 4);
                auto mma_block = [&](auto first) {
                    if constexpr (decltype(first)::value) mbar_wait(sb + BAR_XF, 0);
                    mbar_wait(sb + BAR_WF + 8 * sl[0], par[0]);
                    TLP(28, threadIdx.x == 0 && b == 0);
                    if (b > 0) bar_sync(1 + (b & 1), 256);
                    asm volatile("wgmma.fence.sync.aligned;" ::: "memory");
#pragma unroll
                    for (int kc = 0; kc < 4; kc++) {
                        const uint64_t da = descHi | (uint64_t)(((sb + SM_W + sl[kc] * 8192) & 0x3FFFF) >> 4);
                        const uint64_t dbk = db + kc * (XKB >> 4);
                        wgmma_n152(acc, da, dbk, kc != 0);
                        if (kc > 0) {
                            asm volatile("wgmma.commit_group.sync.aligned;" ::: "memory");
                            asm volatile("wgmma.wait_group.sync.aligned 1;" ::: "memory");
                            mbar_arrive_if(sb + BAR_WE + 8 * sl[kc > 0 ? kc - 1 : 0], lane == 0);
                            mbar_arrive_if(sb + BAR_XE + 8 * (kc > 0 ? kc - 1 : 0), lane == 0 && b == 7);
                        }
                        wgmma_n152(acc, da + (2048 >> 4), dbk + (32 >> 4), 1);
                        wgmma_n152(acc, da + 2 * (2048 >> 4), dbk + 2 * (32 >> 4), 1);
                        if (kc < 3) {
                            if constexpr (decltype(first)::value) mbar_wait(sb + BAR_XF + 8 * (kc + 1), 0);
                            mbar_wait(sb + BAR_WF + 8 * sl[kc < 3 ? kc + 1 : 3], par[kc < 3 ? kc + 1 : 3]);
                            asm volatile("wgmma.fence.sync.aligned;" ::: "memory");
                        }
                        wgmma_n152(acc, da + 3 * (2048 >> 4), dbk + 3 * (32 >> 4), 1);
                        asm volatile("wgmma.commit_group.sync.aligned;" ::: "memory");
                    }
                };
                if (b < 2) mma_block(TrueT{}); else mma_block(FalseT{});
                asm volatile("{\n.reg .pred p;\nsetp.lt.s32 p, %1, 7;\n@p bar.arrive %0, 256;\n}" ::"r"(1 + ((b + 1) & 1)), "r"(b) : "memory");
                if (b >= 2 && b < 6 && (threadIdx.x & 127) == 0) {
                    if (b < 4) {
                        asm volatile("cp.async.bulk.wait_group.read 0;" ::: "memory");
                    } else {
                        asm volatile("cp.async.bulk.wait_group 0;" ::: "memory");
                        mbar_arrive(sb + BAR_STF + 8 * wg);
                        mbar_arrive(sb + BAR_TD);
                    }
                }
                __syncwarp();
                if (b >= 2 && b < 4) bar_sync(6 + wg, 128);
                if (b >= 4) {
                    if (b < 6) mbar_wait_cluster(sb + BAR_PSF, 0);
                    mbar_wait(sb + BAR_STF + 8 * ((b - 4) >> 1), 0);
                    mbar_wait(sb + BAR_STF + 8 * min((b - 3) >> 1, 1), 0);
                    if (b > 4) bar_sync(9 + ((b - 5) & 1), 256);
                }
                asm volatile("wgmma.wait_group.sync.aligned 0;" ::: "memory");
#pragma unroll
                for (int j = 0; j < 76; j++) asm volatile("" : "+f"(acc[j])::"memory");
                mbar_arrive_if(sb + BAR_WE + 8 * sl[3], lane == 0);
                mbar_arrive_if(sb + BAR_XE + 8 * 3, lane == 0 && b >= 6);
#pragma unroll
                for (int kc = 0; kc < 3; kc++) mbar_arrive_if(sb + BAR_XE + 8 * kc, lane == 0 && b == 6);
                slot += 8;
                wphase ^= 1;
                slot -= NWS;
                if (slot >= NWS) { slot -= NWS; wphase ^= 1; }
                TLP(8 + b, (threadIdx.x & 127) == 0);
                if (b < 4) {
                    const uint32_t stg = shalf + wg * XKB;
                    const uint32_t a = stg + stn * 128 + ((stc ^ (stn & 7)) << 4);
#pragma unroll
                    for (int i = 0; i < 18; i += 2)
                        stsm4t(a + i * 1024, pack_bf16(acc[4 * i], acc[4 * i + 1]), pack_bf16(acc[4 * i + 2], acc[4 * i + 3]),
                               pack_bf16(acc[4 * i + 4], acc[4 * i + 5]), pack_bf16(acc[4 * i + 6], acc[4 * i + 7]));
                    stsm2t(a + 18 * 1024, pack_bf16(acc[72], acc[73]), pack_bf16(acc[74], acc[75]));
                    asm volatile("fence.proxy.async.shared::cta;" ::: "memory");
                    bar_sync(6 + wg, 128);
                    if ((threadIdx.x & 127) == 0) {
                        tma_store3d(&tmT, stg, prow0, 4 * rank + b);
                        asm volatile("cp.async.bulk.commit_group;" ::: "memory");
                    }
                    __syncwarp();
                } else {
                    const uint32_t blk = SM_S + rank * SHALF + (b - 4) * SBLK;
                    const uint32_t xch = b < 7 ? sb + blk + SBLK : sb + SM_W;
                    const int own0 = rank * p.npc, peer0 = p.npc - own0;
#pragma unroll
                    for (int i = 0; i < 19; i += 2) {
                        const int nd = 8 * i + stn, row = nd - own0, prow = nd - peer0;
                        const bool own = (unsigned)row < (unsigned)p.npc;
                        const int r = own ? row : prow;
                        const uint32_t a = own || (unsigned)prow < (unsigned)p.npc
                                               ? (own ? sb + blk : xch) + r * 128 + ((stc ^ (r & 7)) << 4)
                                               : sb + SM_DUMMY + (lane & 7) * 16;
                        if (i < 18)
                            stsm4t(a, pack_bf16(acc[4 * i], acc[4 * i + 1]), pack_bf16(acc[4 * i + 2], acc[4 * i + 3]),
                                   pack_bf16(acc[4 * i + 4], acc[4 * i + 5]), pack_bf16(acc[4 * i + 6], acc[4 * i + 7]));
                        else
                            stsm2t(a, pack_bf16(acc[4 * i], acc[4 * i + 1]), pack_bf16(acc[4 * i + 2], acc[4 * i + 3]));
                    }
                    bar_sync(6 + wg, 128);
                    {
                        const int t = threadIdx.x & 127, nun = p.npc * 8;
                        uint4 v[5];
#pragma unroll
                        for (int k = 0; k < 5; k++)
                            if (t + 128 * k < nun) v[k] = lds128(xch + (t + 128 * k) * 16);
#pragma unroll
                        for (int k = 0; k < 5; k++)
                            if (t + 128 * k < nun)
                                asm volatile("st.async.weak.shared::cluster.mbarrier::complete_tx::bytes.v4.b32 [%0], {%1,%2,%3,%4}, [%5];"
                                             ::"r"(peer_sb + blk + (t + 128 * k) * 16),
                                               "r"(v[k].x), "r"(v[k].y), "r"(v[k].z), "r"(v[k].w), "r"(peer_sb + BAR_SR) : "memory");
                    }
                    if (b < 7) bar_arrive(9 + ((b - 4) & 1), 256);
                    TLP(12 + b, (threadIdx.x & 127) == 0);
                }
            }
        }
        if (lane == 0) mbar_arrive(sb + BAR_GD);
        TLP(1, threadIdx.x == 0);
        const int g8 = lane >> 2, q = lane & 3;
        const int f0 = warp * 32;
        uint32_t cf[2][4];
#pragma unroll
        for (int m = 0; m < 2; m++) {
#pragma unroll
            for (int a = 0; a < 4; a++) {
                const int f = f0 + 16 * m + g8 + (a & 1) * 8;
                const int k = 2 * q + (a >> 1) * 8;
                const float lo = __bfloat162float(p.cw[k * D + f]) * 0.5f;
                const float hi = __bfloat162float(p.cw[(k + 1) * D + f]) * 0.5f;
                cf[m][a] = pack_bf16(lo, hi);
            }
        }
        const uint32_t ipat = (g8 >> 1) == q ? (0x3F80u << ((g8 & 1) * 16)) : 0u;
        const uint32_t ihalf = (g8 >> 1) == q ? (0x3F00u << ((g8 & 1) * 16)) : 0u;
        const int mat = lane >> 3, mh = mat & 1;
        const int erow = (mat >> 1) * 8 + (lane & 7);
        const int ch0 = 4 * warp + mh;
        const uint32_t offA = erow * ROWB + (ch0 >> 3) * 128 + (((ch0 & 7) ^ (erow & 7)) << 4);
        const uint32_t offE = METAO + erow * 64 + ((mh ^ ((erow >> 1) & 3)) << 4);
        const int trow = mh * 8 + (lane & 7);
        const uint32_t offT = METAO + trow * 64 + (((2 + (mat >> 1)) ^ ((trow >> 1) & 3)) << 4);
        const uint32_t outs = sb + SM_OUT + warp * OUTW;

        bar_sync(8, NCONS * 32);
        mbar_wait_cluster(sb + BAR_SR, 0);
        mbar_wait(sb + BAR_CNT, 0);
        uint32_t st = sb, fb = sb + BAR_FULL, phase = 0;
        auto advance = [&] {
            if (lane == 0) mbar_arrive(fb + (BAR_EMPTY - BAR_FULL));
            st += STAGEB; fb += 8;
            if (fb == sb + BAR_FULL + 8 * NST) { st = sb; fb = sb + BAR_FULL; phase ^= 1; }
        };
        const int ngv = min(p.ng, (n1 - n0 + 15) >> 4);
        uint32_t ha[2][4];
        float d2[2][2][4];
        auto s_addr = [&](int g) {
            const int row = min(16 * g + erow, p.npc - 1);
            return sb + SM_S + (warp >> 1) * SBLK + row * 128 + (((ch0 & 7) ^ (row & 7)) << 4);
        };
        auto load_ha = [&](int g) {
            const uint32_t a = s_addr(g);
            ldsm4t(ha[0], a);
            ldsm4t(ha[1], a ^ 32);
        };
        auto init_agg = [&](int g) {
            const uint32_t a = s_addr(g) + 4 * SBLK;
#pragma unroll
            for (int m = 0; m < 2; m++) {
                uint32_t hu[4];
                ldsm4t(hu, a ^ (32 * m));
                mma8z(d2[m][0], hu[0], hu[1], ipat);
                mma8z(d2[m][1], hu[2], hu[3], ipat);
            }
        };
        auto finish = [&](int g) {
            const int gn0 = n0 + 16 * g;
#pragma unroll
            for (int m = 0; m < 2; m++) {
                uint32_t o[4];
#pragma unroll
                for (int n = 0; n < 2; n++) {
                    float y[4];
#pragma unroll
                    for (int k = 0; k < 4; k++) {
                        const float h = 0.5f * d2[m][n][k];
                        y[k] = fmaf(h, tanh_fast(h), h);
                    }
                    o[2 * n] = pack_bf16(y[0], y[1]);
                    o[2 * n + 1] = pack_bf16(y[2], y[3]);
                }
                stsm4t(outs + erow * 80 + 32 * m + mh * 16, o[0], o[1], o[2], o[3]);
            }
            __syncwarp();
#pragma unroll
            for (int i = 0; i < 2; i++) {
                const int nd = (lane >> 2) + 8 * i;
                const uint4 v = lds128(outs + nd * 80 + (lane & 3) * 16);
                if (gn0 + nd < n1) *reinterpret_cast<uint4*>(p.out + (size_t)(gn0 + nd) * D + f0 + (lane & 3) * 8) = v;
            }
            __syncwarp();
        };
        struct Buf { uint32_t hv[2][4]; uint32_t oht[4]; float z[2][2][4]; };
        auto load_gate = [&](Buf& n, auto&& between) {
            mbar_wait(fb, phase);
            const uint32_t a0 = st + offA, a1 = a0 ^ 32, ae = st + offE;
            uint32_t eb[4], oh[4], hb[2][4];
            ldsm4(eb, ae);
            ldsm4(oh, ae ^ 32);
            ldsm4t(hb[0], a0);
            ldsm4t(hb[1], a1);
            ldsm4t(n.oht, st + offT);
            ldsm4t(n.hv[0], a0 + 512);
            ldsm4t(n.hv[1], a1 + 512);
            advance();
            between();
#pragma unroll
            for (int m = 0; m < 2; m++) {
                mma16z(n.z[m][0], cf[m], eb[0], eb[1]);
                mma16z(n.z[m][1], cf[m], eb[2], eb[3]);
                mma16(n.z[m][0], ha[m], oh[0], oh[1]);
                mma16(n.z[m][1], ha[m], oh[2], oh[3]);
                mma8(n.z[m][0], hb[m][0], hb[m][1], ihalf);
                mma8(n.z[m][1], hb[m][2], hb[m][3], ihalf);
            }
        };
        auto message = [&](const Buf& c) {
#pragma unroll
            for (int m = 0; m < 2; m++) {
                uint32_t msg[4];
                msg[0] = fma_bf16x2(pack_bf16(tanh_fast(c.z[m][0][0]), tanh_fast(c.z[m][0][1])), c.hv[m][0], c.hv[m][0]);
                msg[1] = fma_bf16x2(pack_bf16(tanh_fast(c.z[m][0][2]), tanh_fast(c.z[m][0][3])), c.hv[m][1], c.hv[m][1]);
                msg[2] = fma_bf16x2(pack_bf16(tanh_fast(c.z[m][1][0]), tanh_fast(c.z[m][1][1])), c.hv[m][2], c.hv[m][2]);
                msg[3] = fma_bf16x2(pack_bf16(tanh_fast(c.z[m][1][2]), tanh_fast(c.z[m][1][3])), c.hv[m][3], c.hv[m][3]);
                mma16(d2[m][0], msg, c.oht[0], c.oht[1]);
                mma16(d2[m][1], msg, c.oht[2], c.oht[3]);
            }
        };
        for (int g = 0; g < ngv; g++) {
            const int cnt = s_cnt[g];
            load_ha(g);
            init_agg(g);
            if (cnt > 0) {
                Buf A, B;
                load_gate(A, [] {});
                int rem = cnt - 16;
                while (rem > 16) {
                    load_gate(B, [&] { message(A); });
                    load_gate(A, [&] { message(B); });
                    rem -= 32;
                }
                if (rem > 0) {
                    load_gate(B, [&] { message(A); });
                    message(B);
                } else {
                    message(A);
                }
            }
            finish(g);
        }
        TLP(3, threadIdx.x == 0);
    } else {
        const int pw = warp - NCONS;
        if (pw == 0) {
            if (lane == 0) {
                const unsigned target = (ld_acquire(p.barB) / G + 1) * G;
                bool arrived = false;
                int slot = 0, ph = 0;
                for (int i = NWS; i < 32; i++) {
                    mbar_wait(sb + BAR_WE + 8 * slot, ph);
                    load_w(i, slot);
                    if (++slot == NWS) { slot = 0; ph ^= 1; }
                    if (!arrived && mbar_test(sb + BAR_TD, 0)) {
                        asm volatile("red.release.gpu.global.add.u32 [%0], 1;" ::"l"(p.barB) : "memory");
                        arrived = true;
                        TL(4);
                    }
                }
                if (!arrived) {
                    mbar_wait(sb + BAR_TD, 0);
                    asm volatile("red.release.gpu.global.add.u32 [%0], 1;" ::"l"(p.barB) : "memory");
                    TL(4);
                }
                grid_wait(p.barB, target);
                TL(5);
                mbar_arrive(sb + BAR_GO);
            }
            __syncwarp();
        } else {
            const int t = threadIdx.x - (NCONS + 1) * 32;
            if (t == 0) {
                asm volatile("mbarrier.arrive.relaxed.cluster.shared::cluster.b64 _, [%0];" ::"r"(mapa(sb + BAR_PSF, rank ^ 1)) : "memory");
                TL(6);
                const unsigned target = grid_arrive(p.barA);
                grid_wait(p.barA, target);
                TL(7);
            }
            bar_sync(4, NB2);
            int* s_g = reinterpret_cast<int*>(smem_raw + SM_CNT);
            bool slow;
            {
                constexpr int NIT = (GMAX + 2 * NW2 - 1) / (2 * NW2);
                const int w3 = pw - 1, slot = lane & 15, hs = (lane >> 4) * 16;
                const int src0 = 2 * w3 + (lane >> 4);
                const int2* box = &p.inbox[(c * G + src0) * PAIR + slot];
                int2 rv[NIT];
#pragma unroll
                for (int i = 0; i < NIT; i++) rv[i] = 2 * NW2 * i + src0 < G ? __ldcg(box + 2 * NW2 * i * PAIR) : make_int2(0, 0);
                uint32_t lo = 0, hi = 0, vmask = 0, big = 0;
                bool over = false;
#pragma unroll
                for (int i = 0; i < NIT; i++) {
                    const uint32_t both = __reduce_add_sync(0xffffffffu, slot == 0 ? (uint32_t)min(rv[i].x, 0xFFFF) << hs : 0u);
                    const int tot = (both >> hs) & 0xFFFF;
                    over |= tot >= PAIR;
                    const bool valid = tot < PAIR && slot >= 1 && slot <= tot;
                    big |= (tot < PAIR && 16 + slot <= tot) ? 1u << i : 0u;
                    vmask |= valid ? 1u << i : 0u;
                    const int g = rv[i].y >> 22;
                    lo += valid && g < 3 ? 1u << (10 * g) : 0u;
                    hi += valid && g >= 3 ? 1u << (10 * (g - 3)) : 0u;
                }
                if (t == 0) { if (lo == 0x7FFFFFFF) TL(24); TL(24); }
                int2 w0 = make_int2(0, 0);
                if (big) w0 = __ldcg(box + 2 * NW2 * (__ffs(big) - 1) * PAIR + 16);
                uint32_t slo = lo, shi = hi;
#pragma unroll
                for (int d = 1; d < 32; d <<= 1) {
                    const uint32_t u = __shfl_up_sync(0xffffffffu, slo, d), v = __shfl_up_sync(0xffffffffu, shi, d);
                    if (lane >= d) { slo += u; shi += v; }
                }
                uint32_t* s_wt = reinterpret_cast<uint32_t*>(smem_raw + SM_SLOT);
                if (lane == 31) { s_wt[2 * w3] = slo; s_wt[2 * w3 + 1] = shi; }
                if (__any_sync(0xffffffffu, over) && lane == 0) s_g[MAXNG] = 1;
                bar_sync(4, NB2);
                if (t == 0) TL(25);
                slo -= lo; shi -= hi;
                {
                    int gt = 0;
                    const int sh = t < 3 ? 10 * t : 10 * (t - 3);
#pragma unroll
                    for (int w = 0; w < NW2; w++) {
                        const uint32_t l = s_wt[2 * w], h = s_wt[2 * w + 1];
                        if (w < w3) { slo += l; shi += h; }
                        gt += ((t < 3 ? l : h) >> (sh & 31)) & 1023;
                    }
                    if (t < MAXNG) s_g[t] = gt;
                }
                unsigned* s_roff = reinterpret_cast<unsigned*>(smem_raw + SM_ROFF);
                unsigned* s_rmeta = reinterpret_cast<unsigned*>(smem_raw + SM_RMETA);
#pragma unroll
                for (int i = 0; i < NIT; i++) {
                    const bool valid = (vmask >> i) & 1;
                    const uint32_t r = (uint32_t)rv[i].y >> 18, g = r >> 4;
                    const bool glo = g < 3;
                    const uint32_t sh = 10 * g - (glo ? 0 : 30);
                    const uint32_t pos = ((glo ? slo : shi) >> (sh & 31)) & 1023;
                    const uint32_t inc = valid ? 1u << (sh & 31) : 0u;
                    slo += glo ? inc : 0u;
                    shi += glo ? 0u : inc;
                    const uint32_t a = sb + SM_ROFF + 4 * (g * p.capg + pos);
                    asm volatile("{\n.reg .pred q;\nsetp.ne.u32 q, %3, 0;\n@q st.shared.u32 [%0], %1;\n@q st.shared.u32 [%0 + %4], %2;\n}"
                                 ::"r"(a), "r"((unsigned)rv[i].x * 1024u), "r"((rv[i].y & 0x3FFFF) | ((r & 15) << 18)),
                                   "r"((uint32_t)(valid && pos < (uint32_t)p.capg)), "n"(SM_RMETA - SM_ROFF) : "memory");
                }
                bar_sync(4, NB2);
                if (t == 0) TL(29);
                bool first = true;
                while (big) {
                    const int i = __ffs(big) - 1;
                    big &= big - 1;
                    const int2 v = first ? w0 : __ldcg(box + 2 * NW2 * i * PAIR + 16);
                    first = false;
                    const int r = v.y >> 18, ps = atomicAdd(&s_g[r >> 4], 1);
                    if (ps < p.capg) {
                        s_roff[(r >> 4) * p.capg + ps] = (unsigned)v.x * 1024u;
                        s_rmeta[(r >> 4) * p.capg + ps] = (v.y & 0x3FFFF) | ((r & 15) << 18);
                    }
                }
                bar_sync(4, NB2);
                slow = s_g[MAXNG] != 0;
                for (int g = 0; g < p.ng; g++) slow |= s_g[g] > p.capg;
            }
            if (slow) {
                bar_sync(4, NB2);
                if (t < MAXNG) s_g[t] = 0;
                if (t == 0) s_g[MAXNG] = 1;
                bar_sync(4, NB2);
                for (int e = t; e < p.E; e += NB2) {
                    const int d = __ldg(p.dst + e);
                    if (d >= n0 && d < n1) atomicAdd(&s_g[(d - n0) >> 4], 1);
                }
            }
            bar_sync(4, NB2);
            if (t == 0) { TL(20); mbar_arrive(sb + BAR_CNT); }
        }
        const int gp = pw - GP0;
        if (gp < 0 || gp >= NPROD) {
            return;
        }
        mbar_wait(sb + BAR_CNT, 0);
        const bool slow = s_cnt[MAXNG] != 0;
        const int ngv = min(p.ng, (n1 - n0 + 15) >> 4);
        if (!slow) {
            uint32_t sw[8];
#pragma unroll
            for (int k = 0; k < 8; k++) sw[k] = (lane >> 3) * 128 + (((lane & 7) ^ k) << 4);
            const char* tb16 = p.tabT + lane * 16;
            int g = 0, j = gp;
            int cn = ngv > 0 ? s_cnt[0] : 0, nch = (cn + 15) >> 4;
            uint32_t stage = gp % NST, phase = (gp / NST) & 1;
            static_assert(4 * STAGEB <= 4 * XKB && STAGEB <= XKB, "ring stage s < 4 lies in the k blocks 0..s of x");
            int it = gp;
            mbar_wait(sb + BAR_GO, 0);
            if (gp == 0 && lane == 0) TL(21);
            while (true) {
                while (g < ngv && j >= nch) { j -= nch; g++; cn = g < ngv ? s_cnt[g] : 0; nch = (cn + 15) >> 4; }
                if (g >= ngv) break;
                const uint32_t st = sb + stage * STAGEB, fb = sb + BAR_FULL + 8 * stage;
                if (it < NST) mbar_wait(it < 4 ? sb + BAR_XE + 8 * it : sb + BAR_GD, 0);
                it += NPROD;
                const int slot0 = g * p.capg + 16 * j;
                const int nv = cn - 16 * j;
                if (nv >= 16) {
                    const uint32_t ra = sb + SM_ROFF + 4 * slot0;
                    const uint4 o0 = lds128(ra), o1 = lds128(ra + 16), o2 = lds128(ra + 32), o3 = lds128(ra + 48);
                    uint32_t meta;
                    asm volatile("ld.shared.u32 %0, [%1];" : "=r"(meta) : "r"(sb + SM_RMETA + 4 * (slot0 + (lane >> 1))));
                    const uint32_t of[16] = {o0.x, o0.y, o0.z, o0.w, o1.x, o1.y, o1.z, o1.w,
                                             o2.x, o2.y, o2.z, o2.w, o3.x, o3.y, o3.z, o3.w};
                    mbar_wait(fb + (BAR_EMPTY - BAR_FULL), phase ^ 1);
#pragma unroll
                    for (int k = 0; k < 16; k++) copy_row(st + sw[k & 7] + k * ROWB, tb16 + of[k]);
                    put_meta(p, st, meta, true, lane);
                    chunk_done(fb, lane);
                } else {
                    uint32_t roff = 0, rmeta = 0;
                    if (lane < nv) {
                        roff = *reinterpret_cast<const unsigned*>(smem_raw + SM_ROFF + 4 * (slot0 + lane));
                        rmeta = *reinterpret_cast<const unsigned*>(smem_raw + SM_RMETA + 4 * (slot0 + lane));
                    }
                    mbar_wait(fb + (BAR_EMPTY - BAR_FULL), phase ^ 1);
                    issue_partial_chunk(p, st, fb, roff, rmeta, nv, lane);
                }
                j += NPROD;
                stage += NPROD;
                if (stage >= NST) { stage -= NST; phase ^= 1; }
            }
        } else if (gp == 0) {
            mbar_wait(sb + BAR_GD, 0);
            mbar_wait(sb + BAR_GO, 0);
            volatile int* s_slot = reinterpret_cast<volatile int*>(smem_raw + SM_SLOT);
            int i = 0;
            for (int g = 0; g < ngv; g++) {
                const int gn0 = n0 + 16 * g, gn1 = min(gn0 + 16, n1);
                const int cn = s_cnt[g];
                int cursor = 0;
                for (int j = 0; 16 * j < cn; j++, i++) {
                    const int stage = i % NST;
                    uint32_t roff = 0, rmeta = 0;
                    const int nv = min(16, cn - 16 * j);
                    int filled = 0;
                    while (filled < nv && cursor < p.E) {
                        const int idx = cursor + lane;
                        const int d = idx < p.E ? __ldg(p.dst + idx) : -1;
                        const bool hit = d >= gn0 && d < gn1;
                        const unsigned mm = __ballot_sync(0xffffffffu, hit);
                        const int slot = filled + __popc(mm & ((1u << lane) - 1));
                        const bool take = hit && slot < nv;
                        if (take) s_slot[slot] = idx;
                        const unsigned tk = __ballot_sync(0xffffffffu, take);
                        filled += __popc(tk);
                        cursor = (filled >= nv) ? cursor + (32 - __clz(tk)) : cursor + 32;
                    }
                    __syncwarp();
                    if (lane < nv) {
                        const int e = s_slot[lane];
                        roff = (unsigned)__ldg(p.src + e) * 1024u;
                        rmeta = e | ((__ldg(p.dst + e) - gn0) << 18);
                    }
                    __syncwarp();
                    const uint32_t st = sb + stage * STAGEB, fb = sb + BAR_FULL + 8 * stage;
                    mbar_wait(fb + (BAR_EMPTY - BAR_FULL), ((i / NST) & 1) ^ 1);
                    issue_partial_chunk(p, st, fb, roff, rmeta, nv, lane);
                }
            }
        }
    }
}

typedef CUresult (*EncodeTiledFn)(CUtensorMap*, CUtensorMapDataType, cuuint32_t, void*, const cuuint64_t*, const cuuint64_t*,
                                  const cuuint32_t*, const cuuint32_t*, CUtensorMapInterleave, CUtensorMapSwizzle,
                                  CUtensorMapL2promotion, CUtensorMapFloatOOBfill);

#define XPROMO CU_TENSOR_MAP_L2_PROMOTION_L2_128B
bool make_map(EncodeTiledFn fn, CUtensorMap* m, const void* ptr, uint64_t rows, uint64_t cols, uint32_t box_rows) {
    cuuint64_t dims[3] = {64, rows, cols / 64};
    cuuint64_t strides[2] = {cols * 2, 128};
    cuuint32_t box[3] = {64, box_rows, 1};
    cuuint32_t estr[3] = {1, 1, 1};
    return fn(m, CU_TENSOR_MAP_DATA_TYPE_BFLOAT16, 3, const_cast<void*>(ptr), dims, strides, box, estr,
              CU_TENSOR_MAP_INTERLEAVE_NONE, CU_TENSOR_MAP_SWIZZLE_128B, XPROMO,
              CU_TENSOR_MAP_FLOAT_OOB_FILL_NONE) == CUDA_SUCCESS;
}

}

extern "C" void kernel_launch(void* const* d_in, const int* in_sizes, int n_in, void* d_out, int out_size) {
    const __nv_bfloat16* x = (const __nv_bfloat16*)d_in[0];
    const __nv_bfloat16* e_attr = (const __nv_bfloat16*)d_in[1];
    const int* src = (const int*)d_in[2];
    const int* dst = (const int*)d_in[3];
    const __nv_bfloat16* u_w = (const __nv_bfloat16*)d_in[4];
    const __nv_bfloat16* v_w = (const __nv_bfloat16*)d_in[5];
    const __nv_bfloat16* g_w = (const __nv_bfloat16*)d_in[6];
    const int N = in_sizes[0] / D, E = in_sizes[2];

    static EncodeTiledFn enc = nullptr;
    static int sms = 0;
    static void *tptr = nullptr, *iptr = nullptr, *aptr = nullptr, *bptr = nullptr;
    if (!enc) {
        void* fn = nullptr;
        cudaDriverEntryPointQueryResult qr;
        if (cudaGetDriverEntryPoint("cuTensorMapEncodeTiled", &fn, cudaEnableDefault, &qr) != cudaSuccess || !fn) return;
        int dev = 0;
        cudaGetDevice(&dev);
        cudaDeviceGetAttribute(&sms, cudaDevAttrMultiProcessorCount, dev);
        cudaFuncSetAttribute(mpnn_fused_kernel, cudaFuncAttributeMaxDynamicSharedMemorySize, SM_ALLOC);
        cudaGetSymbolAddress(&tptr, g_T);
        cudaGetSymbolAddress(&iptr, g_inbox);
        cudaGetSymbolAddress(&aptr, g_barA);
        cudaGetSymbolAddress(&bptr, g_barB);
        enc = (EncodeTiledFn)fn;
    }
    const int G = min(sms, GMAX) & ~1;
    Params p;
    p.e_attr = e_attr; p.src = src; p.dst = dst; p.cw = g_w + 512 * D; p.out = (__nv_bfloat16*)d_out;
    p.tabT = (const char*)tptr;
    p.inbox = (int2*)iptr; p.barA = (unsigned*)aptr; p.barB = (unsigned*)bptr;
    p.wG = (const char*)g_w; p.wV = (const char*)v_w; p.wU = (const char*)u_w;
    p.N = N; p.E = E;
    p.npc = (N + G - 1) / G; p.ng = (p.npc + 15) / 16; p.epc = (E + G - 1) / G;
    p.magic = (unsigned)((0x100000000ull + p.npc - 1) / p.npc);
    p.capg = min((REC_SLOTS / p.ng) & ~15, 1008);
    const int trows = (G / 2 - 1) * 2 * p.npc + NPAIR;
    if (p.npc > NPC_MAX || p.npc < 8 || p.epc > NBIN * EPT || trows > NPAD_MAX || E > (1 << 18) || G < 2) return;

    CUtensorMap tmX, tmG, tmV, tmU, tmT;
    if (!make_map(enc, &tmX, x, N, D, NPAIR) || !make_map(enc, &tmG, g_w, 2 * D + DE, D, 64) || !make_map(enc, &tmV, v_w, D, D, 64) ||
        !make_map(enc, &tmU, u_w, D, D, 64) || !make_map(enc, &tmT, tptr, trows, 512, NPAIR))
        return;
    mpnn_fused_kernel<<<G, NTHREADS, SM_ALLOC>>>(tmX, tmG, tmV, tmU, tmT, p);
}
```

```cpp
#include <cuda_runtime.h>
#include <cuda_bf16.h>
#include <cuda.h>
#include <stdint.h>

namespace {

constexpr int D = 256;
constexpr int DE = 16;
constexpr int NPAD_MAX = 12288;
constexpr int MAXG = 160;
constexpr int GMAX = 132;
constexpr int PAIR = 32;
constexpr int NPAIR = 152;
constexpr int NPC_MAX = 76;
constexpr int MAXNG = 5;

constexpr int NCONS = 8;
constexpr int NW2 = 7;
constexpr int NTHREADS = (NCONS + 1 + NW2) * 32;
constexpr int NPROD = 2;
constexpr int NBIN = NTHREADS - 32;
constexpr int EPT = (1248 + NBIN - 1) / NBIN;
constexpr int NB2 = NW2 * 32;

constexpr int XKB = NPAIR * 128;
constexpr int SM_X = 0;
constexpr int NWS = 7;
constexpr int SM_W = SM_X + 4 * XKB;
constexpr int SM_S = 139264;
constexpr int SBLK = NPC_MAX * 128;
constexpr int SHALF = 4 * SBLK;
constexpr int SM_REC = SM_S + 8 * SBLK;
constexpr int REC_SLOTS = 1760;
constexpr int SM_ROFF = SM_REC;
constexpr int SM_RMETA = SM_REC + 4 * REC_SLOTS;
constexpr int SM_BAR = SM_REC + 8 * REC_SLOTS;
constexpr int ROWB = 1024;
constexpr int METAO = 16 * ROWB;
constexpr int STAGEB = 16 * ROWB + 16 * 64;
constexpr int NST = 8;
static_assert(NST * STAGEB <= SM_S && SM_W + NWS * 8192 <= SM_S && SM_S % 1024 == 0, "smem overlap");
constexpr int SC_STG = 0;
constexpr int SC_HIST = SC_STG + GMAX * PAIR * 8;
static_assert(SC_HIST + 4 * MAXG <= SHALF, "binning scratch too large");
constexpr int BAR_FULL = SM_BAR;
constexpr int BAR_EMPTY = BAR_FULL + 8 * NST;
constexpr int BAR_WF = BAR_EMPTY + 8 * NST;
constexpr int BAR_WE = BAR_WF + 8 * NWS;
constexpr int BAR_XF = BAR_WE + 8 * NWS;
constexpr int BAR_CNT = BAR_XF + 8 * 4;
constexpr int BAR_GO = BAR_CNT + 8;
constexpr int BAR_STF = BAR_GO + 8;
constexpr int BAR_TD = BAR_STF + 16;
constexpr int BAR_PSF = BAR_TD + 8;
constexpr int BAR_SR = BAR_PSF + 8;
constexpr int BAR_GD = BAR_SR + 8;
constexpr int BAR_XE = BAR_GD + 8;
constexpr int SM_CNT = BAR_XE + 8 * 4;
constexpr int SM_SLOT = SM_CNT + 4 * 8;
constexpr int SM_DUMMY = (SM_SLOT + 64 + 127) / 128 * 128;
constexpr int SM_TOTAL = SM_DUMMY + 128;
static_assert(SM_TOTAL % 8 == 0 && SM_TOTAL <= 232448, "smem too large");

struct Params {
    const __nv_bfloat16* e_attr;
    const int* src;
    const int* dst;
    const __nv_bfloat16* cw;
    __nv_bfloat16* out;
    const char* tabT;
    const char *wG, *wV, *wU;
    int2* inbox;
    unsigned *barA, *barB;
    int N, E;
    int npc, ng, epc, capg;
    unsigned magic;
};

__device__ __nv_bfloat16 g_T[NPAD_MAX * 512];
__device__ int2 g_inbox[MAXG * MAXG * PAIR];
__device__ unsigned g_barA[32];
__device__ unsigned g_barB[32];

constexpr int SM_ALLOC = SM_TOTAL;

__device__ __forceinline__ void mbar_init(uint32_t bar, uint32_t cnt) {
    asm volatile("mbarrier.init.shared::cta.b64 [%0], %1;" ::"r"(bar), "r"(cnt) : "memory");
}
__device__ __forceinline__ void mbar_expect_tx(uint32_t bar, uint32_t bytes) {
    asm volatile("mbarrier.arrive.expect_tx.shared::cta.b64 _, [%0], %1;" ::"r"(bar), "r"(bytes) : "memory");
}
__device__ __forceinline__ void mbar_arrive(uint32_t bar) {
    asm volatile("mbarrier.arrive.shared::cta.b64 _, [%0];" ::"r"(bar) : "memory");
}
__device__ __forceinline__ void mbar_arrive_if(uint32_t bar, bool pred) {
    asm volatile("{\n.reg .pred p;\nsetp.ne.u32 p, %1, 0;\n@p mbarrier.arrive.shared::cta.b64 _, [%0];\n}" ::"r"(bar), "r"((uint32_t)pred) : "memory");
}
__device__ __forceinline__ bool mbar_test(uint32_t bar, uint32_t parity) {
    uint32_t ok;
    asm volatile("{\n.reg .pred p;\nmbarrier.test_wait.parity.shared::cta.b64 p, [%1], %2;\nselp.u32 %0, 1, 0, p;\n}"
                 : "=r"(ok) : "r"(bar), "r"(parity) : "memory");
    return ok != 0;
}
__device__ __forceinline__ void mbar_wait(uint32_t bar, uint32_t parity) {
    asm volatile(
        "{\n.reg .pred p;\n.reg .u32 n;\n"
        "mbarrier.try_wait.parity.shared::cta.b64 p, [%0], %1;\n"
        "@p bra DONE_%=;\n"
        "mov.u32 n, 0;\n"
        "WAIT_%=:\n"
        "mbarrier.try_wait.parity.shared::cta.b64 p, [%0], %1;\n"
        "@p bra DONE_%=;\n"
        "add.u32 n, n, 1;\n"
        "setp.lt.u32 p, n, 4194304;\n"
        "@p bra WAIT_%=;\n"
        "trap;\n"
        "DONE_%=:\n}"
        ::"r"(bar), "r"(parity) : "memory");
}
__device__ __forceinline__ void tma_load3d(uint32_t dst, const CUtensorMap* tm, int row, int blk, uint32_t bar) {
    asm volatile("cp.async.bulk.tensor.3d.shared::cluster.global.tile.mbarrier::complete_tx::bytes [%0], [%1, {%3, %4, %5}], [%2];"
                 ::"r"(dst), "l"(tm), "r"(bar), "r"(0), "r"(row), "r"(blk) : "memory");
}
__device__ __forceinline__ void tma_store3d(const CUtensorMap* tm, uint32_t src, int row, int blk) {
    asm volatile("cp.async.bulk.tensor.3d.global.shared::cta.tile.bulk_group [%0, {%2, %3, %4}], [%1];"
                 ::"l"(tm), "r"(src), "r"(0), "r"(row), "r"(blk) : "memory");
}
__device__ __forceinline__ uint32_t mapa(uint32_t addr, uint32_t rank) {
    uint32_t r;
    asm("mapa.shared::cluster.u32 %0, %1, %2;" : "=r"(r) : "r"(addr), "r"(rank));
    return r;
}
__device__ __forceinline__ void mbar_wait_cluster(uint32_t bar, uint32_t parity) {
    asm volatile(
        "{\n.reg .pred p;\n.reg .u32 n;\n"
        "mov.u32 n, 0;\n"
        "WAIT_%=:\n"
        "mbarrier.try_wait.parity.acquire.cluster.shared::cta.b64 p, [%0], %1;\n"
        "@p bra DONE_%=;\n"
        "add.u32 n, n, 1;\n"
        "setp.lt.u32 p, n, 4194304;\n"
        "@p bra WAIT_%=;\n"
        "trap;\n"
        "DONE_%=:\n}"
        ::"r"(bar), "r"(parity) : "memory");
}
__device__ __forceinline__ void bar_sync(int id, int n) { asm volatile("bar.sync %0, %1;" ::"r"(id), "r"(n) : "memory"); }
__device__ __forceinline__ void bar_arrive(int id, int n) { asm volatile("bar.arrive %0, %1;" ::"r"(id), "r"(n) : "memory"); }

__device__ __forceinline__ void ldsm4(uint32_t (&r)[4], uint32_t addr) {
    asm volatile("ldmatrix.sync.aligned.m8n8.x4.shared.b16 {%0,%1,%2,%3}, [%4];"
                 : "=r"(r[0]), "=r"(r[1]), "=r"(r[2]), "=r"(r[3]) : "r"(addr));
}
__device__ __forceinline__ void ldsm4t(uint32_t (&r)[4], uint32_t addr) {
    asm volatile("ldmatrix.sync.aligned.m8n8.x4.trans.shared.b16 {%0,%1,%2,%3}, [%4];"
                 : "=r"(r[0]), "=r"(r[1]), "=r"(r[2]), "=r"(r[3]) : "r"(addr));
}
__device__ __forceinline__ void stsm4t(uint32_t addr, uint32_t a, uint32_t b, uint32_t c, uint32_t d) {
    asm volatile("stmatrix.sync.aligned.m8n8.x4.trans.shared.b16 [%0], {%1,%2,%3,%4};"
                 ::"r"(addr), "r"(a), "r"(b), "r"(c), "r"(d) : "memory");
}
__device__ __forceinline__ void stsm2t(uint32_t addr, uint32_t a, uint32_t b) {
    asm volatile("stmatrix.sync.aligned.m8n8.x2.trans.shared.b16 [%0], {%1,%2};" ::"r"(addr), "r"(a), "r"(b) : "memory");
}
__device__ __forceinline__ void mma16(float (&d)[4], const uint32_t (&a)[4], uint32_t b0, uint32_t b1) {
    asm("mma.sync.aligned.m16n8k16.row.col.f32.bf16.bf16.f32 {%0,%1,%2,%3}, {%4,%5,%6,%7}, {%8,%9}, {%0,%1,%2,%3};"
        : "+f"(d[0]), "+f"(d[1]), "+f"(d[2]), "+f"(d[3])
        : "r"(a[0]), "r"(a[1]), "r"(a[2]), "r"(a[3]), "r"(b0), "r"(b1));
}
__device__ __forceinline__ void mma16z(float (&d)[4], const uint32_t (&a)[4], uint32_t b0, uint32_t b1) {
    asm("mma.sync.aligned.m16n8k16.row.col.f32.bf16.bf16.f32 {%0,%1,%2,%3}, {%4,%5,%6,%7}, {%8,%9}, {%10,%10,%10,%10};"
        : "=f"(d[0]), "=f"(d[1]), "=f"(d[2]), "=f"(d[3])
        : "r"(a[0]), "r"(a[1]), "r"(a[2]), "r"(a[3]), "r"(b0), "r"(b1), "f"(0.f));
}
__device__ __forceinline__ void mma8(float (&d)[4], uint32_t a0, uint32_t a1, uint32_t b0) {
    asm("mma.sync.aligned.m16n8k8.row.col.f32.bf16.bf16.f32 {%0,%1,%2,%3}, {%4,%5}, {%6}, {%0,%1,%2,%3};"
        : "+f"(d[0]), "+f"(d[1]), "+f"(d[2]), "+f"(d[3])
        : "r"(a0), "r"(a1), "r"(b0));
}
__device__ __forceinline__ void mma8z(float (&d)[4], uint32_t a0, uint32_t a1, uint32_t b0) {
    asm("mma.sync.aligned.m16n8k8.row.col.f32.bf16.bf16.f32 {%0,%1,%2,%3}, {%4,%5}, {%6}, {%7,%7,%7,%7};"
        : "=f"(d[0]), "=f"(d[1]), "=f"(d[2]), "=f"(d[3])
        : "r"(a0), "r"(a1), "r"(b0), "f"(0.f));
}
__device__ __forceinline__ uint32_t pack_bf16(float lo, float hi) {
    uint32_t r;
    asm("cvt.rn.bf16x2.f32 %0, %1, %2;" : "=r"(r) : "f"(hi), "f"(lo));
    return r;
}
__device__ __forceinline__ float tanh_fast(float x) {
    float r;
    asm("tanh.approx.f32 %0, %1;" : "=f"(r) : "f"(x));
    return r;
}
__device__ __forceinline__ uint32_t fma_bf16x2(uint32_t a, uint32_t b, uint32_t c) {
    uint32_t r;
    asm("fma.rn.bf16x2 %0, %1, %2, %3;" : "=r"(r) : "r"(a), "r"(b), "r"(c));
    return r;
}
__device__ __forceinline__ unsigned ld_acquire(const unsigned* p) {
    unsigned v;
    asm volatile("ld.acquire.gpu.global.u32 %0, [%1];" : "=r"(v) : "l"(p) : "memory");
    return v;
}
__device__ __forceinline__ unsigned grid_arrive(unsigned* bar) {
    unsigned old;
    asm volatile("atom.add.release.gpu.global.u32 %0, [%1], 1;" : "=r"(old) : "l"(bar) : "memory");
    return (old / gridDim.x + 1) * gridDim.x;
}
__device__ __forceinline__ void grid_wait(const unsigned* bar, unsigned target) {
    uint32_t spins = 0;
    while ((int)(ld_acquire(bar) - target) < 0) {
        if (++spins > (1u << 22)) __trap();
    }
}

__device__ __forceinline__ void wgmma_n152(float (&d)[76], uint64_t da, uint64_t db, int scale_d) {
    asm volatile(
        "{\n.reg .pred p;\nsetp.ne.b32 p, %78, 0;\n"
        "wgmma.mma_async.sync.aligned.m64n152k16.f32.bf16.bf16 "
        "{%0,%1,%2,%3,%4,%5,%6,%7,%8,%9,%10,%11,%12,%13,%14,%15,%16,%17,%18,%19,%20,%21,%22,%23,%24,%25,%26,%27,%28,%29,%30,%31,%32,%33,%34,%35,%36,%37,%38,%39,%40,%41,%42,%43,%44,%45,%46,%47,%48,%49,%50,%51,%52,%53,%54,%55,%56,%57,%58,%59,%60,%61,%62,%63,%64,%65,%66,%67,%68,%69,%70,%71,%72,%73,%74,%75}, "
        "%76, %77, p, 1, 1, 1, 0;\n}"
        : "+f"(d[0]), "+f"(d[1]), "+f"(d[2]), "+f"(d[3]), "+f"(d[4]), "+f"(d[5]), "+f"(d[6]), "+f"(d[7]), "+f"(d[8]), "+f"(d[9]), "+f"(d[10]), "+f"(d[11]), "+f"(d[12]), "+f"(d[13]), "+f"(d[14]), "+f"(d[15]), "+f"(d[16]), "+f"(d[17]), "+f"(d[18]), "+f"(d[19]), "+f"(d[20]), "+f"(d[21]), "+f"(d[22]), "+f"(d[23]), "+f"(d[24]), "+f"(d[25]), "+f"(d[26]), "+f"(d[27]), "+f"(d[28]), "+f"(d[29]), "+f"(d[30]), "+f"(d[31]), "+f"(d[32]), "+f"(d[33]), "+f"(d[34]), "+f"(d[35]), "+f"(d[36]), "+f"(d[37]), "+f"(d[38]), "+f"(d[39]), "+f"(d[40]), "+f"(d[41]), "+f"(d[42]), "+f"(d[43]), "+f"(d[44]), "+f"(d[45]), "+f"(d[46]), "+f"(d[47]), "+f"(d[48]), "+f"(d[49]), "+f"(d[50]), "+f"(d[51]), "+f"(d[52]), "+f"(d[53]), "+f"(d[54]), "+f"(d[55]), "+f"(d[56]), "+f"(d[57]), "+f"(d[58]), "+f"(d[59]), "+f"(d[60]), "+f"(d[61]), "+f"(d[62]), "+f"(d[63]), "+f"(d[64]), "+f"(d[65]), "+f"(d[66]), "+f"(d[67]), "+f"(d[68]), "+f"(d[69]), "+f"(d[70]), "+f"(d[71]), "+f"(d[72]), "+f"(d[73]), "+f"(d[74]), "+f"(d[75])
        : "l"(da), "l"(db), "r"(scale_d));
}

__device__ __forceinline__ void cp16(uint32_t dst, const void* src) {
    asm volatile("cp.async.cg.shared.global [%0], [%1], 16;" ::"r"(dst), "l"(src) : "memory");
}
__device__ __forceinline__ void sts128(uint32_t a, uint32_t x, uint32_t y, uint32_t z, uint32_t w) {
    asm volatile("st.shared.v4.u32 [%0], {%1,%2,%3,%4};" ::"r"(a), "r"(x), "r"(y), "r"(z), "r"(w) : "memory");
}
__device__ __forceinline__ uint4 lds128(uint32_t a) {
    uint4 v;
    asm volatile("ld.shared.v4.u32 {%0,%1,%2,%3}, [%4];" : "=r"(v.x), "=r"(v.y), "=r"(v.z), "=r"(v.w) : "r"(a));
    return v;
}
__device__ __forceinline__ void chunk_done(uint32_t fullbar, int lane) {
    asm volatile("cp.async.mbarrier.arrive.noinc.shared::cta.b64 [%0];" ::"r"(fullbar) : "memory");
    __syncwarp();
    if (lane == 0) mbar_arrive(fullbar);
}
__device__ __forceinline__ void copy_row(uint32_t dst, const char* src) {
    cp16(dst, src);
    cp16(dst + 512, src + 512);
}
__device__ __forceinline__ void put_meta(const Params& p, uint32_t stage, uint32_t meta, bool valid, int lane) {
    const int slot = lane >> 1, half = lane & 1;
    const uint32_t a = stage + METAO + slot * 64 + ((half ^ ((slot >> 1) & 3)) << 4);
    uint32_t w0 = 0, w1 = 0, w2 = 0, w3 = 0;
    if (valid) {
        cp16(a, reinterpret_cast<const char*>(p.e_attr) + (size_t)(meta & 0x3FFFF) * (DE * 2) + half * 16);
        const uint32_t dl = meta >> 18;
        const uint32_t v = (dl >> 3) == (uint32_t)half ? 0x3F00u << ((dl & 1) * 16) : 0u;
        const uint32_t wi = (dl >> 1) & 3;
        w0 = wi == 0 ? v : 0; w1 = wi == 1 ? v : 0; w2 = wi == 2 ? v : 0; w3 = wi == 3 ? v : 0;
    } else {
        sts128(a, 0, 0, 0, 0);
    }
    sts128(a ^ 32, w0, w1, w2, w3);
}
__device__ __forceinline__ void issue_partial_chunk(const Params& p, uint32_t stage, uint32_t fullbar, uint32_t roff, uint32_t rmeta,
                                                    int nvalid, int lane) {
    const uint32_t sline = stage + (lane >> 3) * 128;
    for (int k = 0; k < 16; k++) {
        const uint32_t off = __shfl_sync(0xffffffffu, roff, k);
        const uint32_t dst = sline + k * ROWB + (((lane & 7) ^ (k & 7)) << 4);
        if (k < nvalid) {
            copy_row(dst, p.tabT + off + lane * 16);
        } else {
            sts128(dst, 0, 0, 0, 0);
            sts128(dst + 512, 0, 0, 0, 0);
        }
    }
    const uint32_t meta = __shfl_sync(0xffffffffu, rmeta, lane >> 1);
    put_meta(p, stage, meta, (lane >> 1) < nvalid, lane);
    chunk_done(fullbar, lane);
}

struct TrueT { static constexpr bool value = true; };
struct FalseT { static constexpr bool value = false; };

__global__ void __cluster_dims__(2, 1, 1) __launch_bounds__(NTHREADS, 1)
mpnn_fused_kernel(const __grid_constant__ CUtensorMap tmX, const __grid_constant__ CUtensorMap tmG,
                  const __grid_constant__ CUtensorMap tmV, const __grid_constant__ CUtensorMap tmU,
                  const __grid_constant__ CUtensorMap tmT, const Params p) {
    extern __shared__ __align__(1024) unsigned char smem_raw[];
    const uint32_t sb = (uint32_t)__cvta_generic_to_shared(smem_raw);
    const int warp = __shfl_sync(0xffffffffu, threadIdx.x >> 5, 0), lane = threadIdx.x & 31;
    const int c = blockIdx.x, G = gridDim.x;
    const int rank = c & 1;
    const int prow0 = (c >> 1) * 2 * p.npc;
    const int n0 = c * p.npc;
    const int n1 = min(n0 + p.npc, p.N);
    volatile int* s_cnt = reinterpret_cast<volatile int*>(smem_raw + SM_CNT);

    auto load_w = [&](int i, int slot) {
        const int b = i >> 2, kc = i & 3;
        const CUtensorMap* tm = rank == 0 ? &tmG : (b < 4 ? &tmV : &tmU);
        const int row = (b < 4 && rank == 0 ? 256 : 0) + kc * 64;
        mbar_expect_tx(sb + BAR_WF + 8 * slot, 8192);
        tma_load3d(sb + SM_W + slot * 8192, tm, row, b & 3, sb + BAR_WF + 8 * slot);
    };
    const int scr = SM_S + (1 - rank) * SHALF;

    const int tb1 = threadIdx.x < NCONS * 32 ? threadIdx.x : threadIdx.x - 32;
    const int e0 = c * p.epc, e1 = min(e0 + p.epc, p.E);
    int dv[EPT], sv[EPT];
    if (warp != NCONS) {
#pragma unroll
        for (int i = 0; i < EPT; i++) {
            const int e = e0 + i * NBIN + tb1;
            dv[i] = e < e1 ? __ldg(p.dst + e) : -1;
            sv[i] = e < e1 ? __ldg(p.src + e) : 0;
        }
        if (tb1 >= 192 && tb1 < 192 + MAXG) *reinterpret_cast<int*>(smem_raw + scr + SC_HIST + 4 * (tb1 - 192)) = 0;
        if (tb1 >= 160 && tb1 < 168) *reinterpret_cast<int*>(smem_raw + SM_CNT + 4 * (tb1 - 160)) = 0;
    } else if (lane == 0) {
        for (int i = c; i < 130; i += G) {
            const char* w = i < 66 ? p.wG + i * 4096 : (i < 98 ? p.wV + (i - 66) * 4096 : p.wU + (i - 98) * 4096);
            asm volatile("cp.async.bulk.prefetch.L2.global [%0], %1;" ::"l"(w), "r"(4096) : "memory");
        }
#pragma unroll
        for (int i = 0; i < NWS; i++) mbar_init(sb + BAR_WF + 8 * i, 1);
#pragma unroll
        for (int i = 0; i < 4; i++) mbar_init(sb + BAR_XF + 8 * i, 1);
        asm volatile("fence.mbarrier_init.release.cluster;" ::: "memory");
#pragma unroll
        for (int kc = 0; kc < 4; kc++) {
            mbar_expect_tx(sb + BAR_XF + 8 * kc, XKB);
            tma_load3d(sb + SM_X + kc * XKB, &tmX, prow0, kc, sb + BAR_XF + 8 * kc);
            load_w(kc, kc);
        }
#pragma unroll
        for (int i = 4; i < NWS; i++) load_w(i, i);
#pragma unroll
        for (int i = 0; i < NST; i++) { mbar_init(sb + BAR_FULL + 8 * i, 33); mbar_init(sb + BAR_EMPTY + 8 * i, NCONS); }
#pragma unroll
        for (int i = 0; i < NWS; i++) mbar_init(sb + BAR_WE + 8 * i, 4);
        mbar_init(sb + BAR_CNT, 1);
        mbar_init(sb + BAR_GO, 1);
        mbar_init(sb + BAR_STF, 1);
        mbar_init(sb + BAR_STF + 8, 1);
        mbar_init(sb + BAR_TD, 2);
        mbar_init(sb + BAR_PSF, 1);
        mbar_init(sb + BAR_SR, 1);
        mbar_init(sb + BAR_GD, NCONS);
#pragma unroll
        for (int i = 0; i < 4; i++) mbar_init(sb + BAR_XE + 8 * i, NCONS);
        mbar_expect_tx(sb + BAR_SR, 4 * p.npc * 128);
        asm volatile("fence.mbarrier_init.release.cluster;" ::: "memory");
    }
    __syncthreads();
    asm volatile("barrier.cluster.arrive.relaxed.aligned;" ::: "memory");

    if (warp == NCONS) asm volatile("barrier.cluster.wait.aligned;" ::: "memory");
    if (warp != NCONS) {
        int2* stg = reinterpret_cast<int2*>(smem_raw + scr + SC_STG);
        int* s_hist = reinterpret_cast<int*>(smem_raw + scr + SC_HIST);
#pragma unroll
        for (int i = 0; i < EPT; i++) {
            const int o = __umulhi((unsigned)max(dv[i], 0), p.magic);
            const int rank_o = dv[i] >= 0 ? atomicAdd(&s_hist[o], 1) : PAIR;
            if (rank_o < PAIR - 1)
                stg[o * PAIR + 1 + rank_o] = make_int2(sv[i], (e0 + i * NBIN + tb1) | ((dv[i] - o * p.npc) << 18));
        }
        asm volatile("barrier.cluster.wait.aligned;" ::: "memory");
        bar_sync(3, NBIN);
        {
            const int k = lane & 15, w = tb1 >> 5;
#pragma unroll
            for (int i = 0; i < (GMAX + NBIN / 16 - 1) / (NBIN / 16); i++) {
                const int o = (NBIN / 16) * i + 2 * w + (lane >> 4);
                if (o < G) {
                    const int tot = s_hist[o];
                    uint4 v = lds128(sb + scr + SC_STG + o * (PAIR * 8) + k * 16);
                    if (k == 0) { v.x = tot; v.y = 0; }
                    if (2 * k <= (min(tot, PAIR - 1) | 3)) *reinterpret_cast<uint4*>(&p.inbox[(o * G + c) * PAIR + 2 * k]) = v;
                }
            }
        }
        if (warp < NCONS) bar_arrive(3, NBIN); else bar_sync(3, NBIN);
    }

    if (warp < NCONS) {
        const int wg = warp >> 2, wj = warp & 3;
        {
            const uint64_t descHi = ((uint64_t)(1024 >> 4) << 32) | (1ull << 62) | (1ull << 16);
            const int stn = (lane & 7) + ((lane >> 4) << 3);
            const int stc = 2 * wj + ((lane >> 3) & 1);
            const uint32_t shalf = sb + SM_S + rank * SHALF;
            const uint32_t peer_sb = mapa(sb, rank ^ 1);
            int slot = 4 * wg, wphase = 0;
            for (int b = wg; b < 8; b += 2) {
                float acc[76];
                uint32_t sl[4], par[4];
#pragma unroll
                for (int kc = 0; kc < 4; kc++) {
                    const int t = slot + kc;
                    sl[kc] = t >= NWS ? t - NWS : t;
                    par[kc] = wphase ^ (t >= NWS);
                }
                const uint64_t db = descHi | (uint64_t)(((sb + SM_X) & 0x3FFFF) >> 4);
                auto mma_block = [&](auto first) {
                    if constexpr (decltype(first)::value) mbar_wait(sb + BAR_XF, 0);
                    mbar_wait(sb + BAR_WF + 8 * sl[0], par[0]);
                    if (b > 0) bar_sync(1 + (b & 1), 256);
                    asm volatile("wgmma.fence.sync.aligned;" ::: "memory");
#pragma unroll
                    for (int kc = 0; kc < 4; kc++) {
                        const uint64_t da = descHi | (uint64_t)(((sb + SM_W + sl[kc] * 8192) & 0x3FFFF) >> 4);
                        const uint64_t dbk = db + kc * (XKB >> 4);
                        wgmma_n152(acc, da, dbk, kc != 0);
                        if (kc > 0) {
                            asm volatile("wgmma.commit_group.sync.aligned;" ::: "memory");
                            asm volatile("wgmma.wait_group.sync.aligned 1;" ::: "memory");
                            mbar_arrive_if(sb + BAR_WE + 8 * sl[kc > 0 ? kc - 1 : 0], lane == 0);
                            mbar_arrive_if(sb + BAR_XE + 8 * (kc > 0 ? kc - 1 : 0), lane == 0 && b == 7);
                        }
                        wgmma_n152(acc, da + (2048 >> 4), dbk + (32 >> 4), 1);
                        wgmma_n152(acc, da + 2 * (2048 >> 4), dbk + 2 * (32 >> 4), 1);
                        if (kc < 3) {
                            if constexpr (decltype(first)::value) mbar_wait(sb + BAR_XF + 8 * (kc + 1), 0);
                            mbar_wait(sb + BAR_WF + 8 * sl[kc < 3 ? kc + 1 : 3], par[kc < 3 ? kc + 1 : 3]);
                            asm volatile("wgmma.fence.sync.aligned;" ::: "memory");
                        }
                        wgmma_n152(acc, da + 3 * (2048 >> 4), dbk + 3 * (32 >> 4), 1);
                        asm volatile("wgmma.commit_group.sync.aligned;" ::: "memory");
                    }
                };
                if (b < 2) mma_block(TrueT{}); else mma_block(FalseT{});
                asm volatile("{\n.reg .pred p;\nsetp.lt.s32 p, %1, 7;\n@p bar.arrive %0, 256;\n}" ::"r"(1 + ((b + 1) & 1)), "r"(b) : "memory");
                if (b >= 2 && b < 6 && (threadIdx.x & 127) == 0) {
                    if (b < 4) {
                        asm volatile("cp.async.bulk.wait_group.read 0;" ::: "memory");
                    } else {
                        asm volatile("cp.async.bulk.wait_group 0;" ::: "memory");
                        mbar_arrive(sb + BAR_STF + 8 * wg);
                        mbar_arrive(sb + BAR_TD);
                    }
                }
                __syncwarp();
                if (b >= 2 && b < 4) bar_sync(6 + wg, 128);
                if (b >= 4) {
                    if (b < 6) mbar_wait_cluster(sb + BAR_PSF, 0);
                    mbar_wait(sb + BAR_STF + 8 * ((b - 4) >> 1), 0);
                    mbar_wait(sb + BAR_STF + 8 * min((b - 3) >> 1, 1), 0);
                    if (b > 4) bar_sync(9 + ((b - 5) & 1), 256);
                }
                asm volatile("wgmma.wait_group.sync.aligned 0;" ::: "memory");
#pragma unroll
                for (int j = 0; j < 76; j++) asm volatile("" : "+f"(acc[j])::"memory");
                mbar_arrive_if(sb + BAR_WE + 8 * sl[3], lane == 0);
                mbar_arrive_if(sb + BAR_XE + 8 * 3, lane == 0 && b >= 6);
#pragma unroll
                for (int kc = 0; kc < 3; kc++) mbar_arrive_if(sb + BAR_XE + 8 * kc, lane == 0 && b == 6);
                slot += 8;
                wphase ^= 1;
                slot -= NWS;
                if (slot >= NWS) { slot -= NWS; wphase ^= 1; }
                if (b < 4) {
                    const uint32_t stg = shalf + wg * XKB;
                    const uint32_t a = stg + stn * 128 + ((stc ^ (stn & 7)) << 4);
#pragma unroll
                    for (int i = 0; i < 18; i += 2)
                        stsm4t(a + i * 1024, pack_bf16(acc[4 * i], acc[4 * i + 1]), pack_bf16(acc[4 * i + 2], acc[4 * i + 3]),
                               pack_bf16(acc[4 * i + 4], acc[4 * i + 5]), pack_bf16(acc[4 * i + 6], acc[4 * i + 7]));
                    stsm2t(a + 18 * 1024, pack_bf16(acc[72], acc[73]), pack_bf16(acc[74], acc[75]));
                    asm volatile("fence.proxy.async.shared::cta;" ::: "memory");
                    bar_sync(6 + wg, 128);
                    if ((threadIdx.x & 127) == 0) {
                        tma_store3d(&tmT, stg, prow0, 4 * rank + b);
                        asm volatile("cp.async.bulk.commit_group;" ::: "memory");
                    }
                    __syncwarp();
                } else {
                    const uint32_t blk = SM_S + rank * SHALF + (b - 4) * SBLK;
                    const uint32_t xch = b < 7 ? sb + blk + SBLK : sb + SM_W;
                    const int own0 = rank * p.npc, peer0 = p.npc - own0;
                    const int ro = stn - own0, rp = stn - peer0;
                    const uint32_t aown = sb + blk + ro * 128 + ((stc ^ (ro & 7)) << 4);
                    const uint32_t apeer = xch + rp * 128 + ((stc ^ (rp & 7)) << 4);
                    const uint32_t asink = sb + SM_DUMMY + (lane & 7) * 16;
#pragma unroll
                    for (int i = 0; i < 19; i += 2) {
                        const uint32_t a = (unsigned)(ro + 8 * i) < (unsigned)p.npc
                                               ? aown + i * 1024
                                               : ((unsigned)(rp + 8 * i) < (unsigned)p.npc ? apeer + i * 1024 : asink);
                        if (i < 18)
                            stsm4t(a, pack_bf16(acc[4 * i], acc[4 * i + 1]), pack_bf16(acc[4 * i + 2], acc[4 * i + 3]),
                                   pack_bf16(acc[4 * i + 4], acc[4 * i + 5]), pack_bf16(acc[4 * i + 6], acc[4 * i + 7]));
                        else
                            stsm2t(a, pack_bf16(acc[4 * i], acc[4 * i + 1]), pack_bf16(acc[4 * i + 2], acc[4 * i + 3]));
                    }
                    bar_sync(6 + wg, 128);
                    {
                        const int t = threadIdx.x & 127, nun = p.npc * 8;
                        uint4 v[5];
#pragma unroll
                        for (int k = 0; k < 5; k++)
                            if (t + 128 * k < nun) v[k] = lds128(xch + (t + 128 * k) * 16);
#pragma unroll
                        for (int k = 0; k < 5; k++)
                            if (t + 128 * k < nun)
                                asm volatile("st.async.weak.shared::cluster.mbarrier::complete_tx::bytes.v4.b32 [%0], {%1,%2,%3,%4}, [%5];"
                                             ::"r"(peer_sb + blk + (t + 128 * k) * 16),
                                               "r"(v[k].x), "r"(v[k].y), "r"(v[k].z), "r"(v[k].w), "r"(peer_sb + BAR_SR) : "memory");
                    }
                    if (b < 7) bar_arrive(9 + ((b - 4) & 1), 256);
                }
            }
        }
        if (lane == 0) mbar_arrive(sb + BAR_GD);
        const int g8 = lane >> 2, q = lane & 3;
        const int f0 = warp * 32;
        uint32_t cf[2][4];
#pragma unroll
        for (int m = 0; m < 2; m++) {
#pragma unroll
            for (int a = 0; a < 4; a++) {
                const int f = f0 + 16 * m + g8 + (a & 1) * 8;
                const int k = 2 * q + (a >> 1) * 8;
                const float lo = __bfloat162float(p.cw[k * D + f]) * 0.5f;
                const float hi = __bfloat162float(p.cw[(k + 1) * D + f]) * 0.5f;
                cf[m][a] = pack_bf16(lo, hi);
            }
        }
        const uint32_t ipat = (g8 >> 1) == q ? (0x3F80u << ((g8 & 1) * 16)) : 0u;
        const uint32_t ihalf = (g8 >> 1) == q ? (0x3F00u << ((g8 & 1) * 16)) : 0u;
        const int mat = lane >> 3, mh = mat & 1;
        const int erow = (mat >> 1) * 8 + (lane & 7);
        const int ch0 = 4 * warp + mh;
        const uint32_t offA = erow * ROWB + (ch0 >> 3) * 128 + (((ch0 & 7) ^ (erow & 7)) << 4);
        const uint32_t offE = METAO + erow * 64 + ((mh ^ ((erow >> 1) & 3)) << 4);
        const int trow = mh * 8 + (lane & 7);
        const uint32_t offT = METAO + trow * 64 + (((2 + (mat >> 1)) ^ ((trow >> 1) & 3)) << 4);

        bar_sync(8, NCONS * 32);
        mbar_wait_cluster(sb + BAR_SR, 0);
        mbar_wait(sb + BAR_CNT, 0);
        uint32_t st = sb, fb = sb + BAR_FULL, phase = 0;
        auto advance = [&] {
            if (lane == 0) mbar_arrive(fb + (BAR_EMPTY - BAR_FULL));
            st += STAGEB; fb += 8;
            if (fb == sb + BAR_FULL + 8 * NST) { st = sb; fb = sb + BAR_FULL; phase ^= 1; }
        };
        const int ngv = min(p.ng, (n1 - n0 + 15) >> 4);
        uint32_t ha[2][4];
        float d2[2][2][4];
        auto s_addr = [&](int g) {
            const int row = min(16 * g + erow, p.npc - 1);
            return sb + SM_S + (warp >> 1) * SBLK + row * 128 + (((ch0 & 7) ^ (row & 7)) << 4);
        };
        auto load_ha = [&](int g) {
            const uint32_t a = s_addr(g);
            ldsm4t(ha[0], a);
            ldsm4t(ha[1], a ^ 32);
        };
        auto init_agg = [&](int g) {
            const uint32_t a = s_addr(g) + 4 * SBLK;
#pragma unroll
            for (int m = 0; m < 2; m++) {
                uint32_t hu[4];
                ldsm4t(hu, a ^ (32 * m));
                mma8z(d2[m][0], hu[0], hu[1], ipat);
                mma8z(d2[m][1], hu[2], hu[3], ipat);
            }
        };
        const uint32_t outs = sb + SM_S + (warp >> 1) * SBLK;
        const uint32_t out_st = outs + erow * 128 + (((ch0 & 7) ^ (erow & 7)) << 4);
        const uint32_t out_ld = outs + (lane >> 2) * 128 + (((4 * (warp & 1) + (lane & 3)) ^ (lane >> 2)) << 4);
        auto finish = [&](int g) {
            const int gn0 = n0 + 16 * g;
#pragma unroll
            for (int m = 0; m < 2; m++) {
                uint32_t o[4];
#pragma unroll
                for (int n = 0; n < 2; n++) {
                    float y[4];
#pragma unroll
                    for (int k = 0; k < 4; k++) {
                        const float h = 0.5f * d2[m][n][k];
                        y[k] = fmaf(h, tanh_fast(h), h);
                    }
                    o[2 * n] = pack_bf16(y[0], y[1]);
                    o[2 * n + 1] = pack_bf16(y[2], y[3]);
                }
                stsm4t(out_st ^ (32 * m), o[0], o[1], o[2], o[3]);
            }
            __syncwarp();
#pragma unroll
            for (int i = 0; i < 2; i++) {
                const int nd = (lane >> 2) + 8 * i;
                const uint4 v = lds128(out_ld + i * 1024);
                if (gn0 + nd < n1) *reinterpret_cast<uint4*>(p.out + (size_t)(gn0 + nd) * D + f0 + (lane & 3) * 8) = v;
            }
            __syncwarp();
        };
        struct Buf { uint32_t hv[2][4]; uint32_t oht[4]; float z[2][2][4]; };
        auto load_gate = [&](Buf& n, auto&& between) {
            mbar_wait(fb, phase);
            const uint32_t a0 = st + offA, a1 = a0 ^ 32, ae = st + offE;
            uint32_t eb[4], oh[4], hb[2][4];
            ldsm4(eb, ae);
            ldsm4(oh, ae ^ 32);
            ldsm4t(hb[0], a0);
            ldsm4t(hb[1], a1);
            ldsm4t(n.oht, st + offT);
            ldsm4t(n.hv[0], a0 + 512);
            ldsm4t(n.hv[1], a1 + 512);
            advance();
            between();
#pragma unroll
            for (int m = 0; m < 2; m++) {
                mma16z(n.z[m][0], cf[m], eb[0], eb[1]);
                mma16z(n.z[m][1], cf[m], eb[2], eb[3]);
                mma16(n.z[m][0], ha[m], oh[0], oh[1]);
                mma16(n.z[m][1], ha[m], oh[2], oh[3]);
                mma8(n.z[m][0], hb[m][0], hb[m][1], ihalf);
                mma8(n.z[m][1], hb[m][2], hb[m][3], ihalf);
            }
        };
        auto message = [&](const Buf& c) {
#pragma unroll
            for (int m = 0; m < 2; m++) {
                uint32_t msg[4];
                msg[0] = fma_bf16x2(pack_bf16(tanh_fast(c.z[m][0][0]), tanh_fast(c.z[m][0][1])), c.hv[m][0], c.hv[m][0]);
                msg[1] = fma_bf16x2(pack_bf16(tanh_fast(c.z[m][0][2]), tanh_fast(c.z[m][0][3])), c.hv[m][1], c.hv[m][1]);
                msg[2] = fma_bf16x2(pack_bf16(tanh_fast(c.z[m][1][0]), tanh_fast(c.z[m][1][1])), c.hv[m][2], c.hv[m][2]);
                msg[3] = fma_bf16x2(pack_bf16(tanh_fast(c.z[m][1][2]), tanh_fast(c.z[m][1][3])), c.hv[m][3], c.hv[m][3]);
                mma16(d2[m][0], msg, c.oht[0], c.oht[1]);
                mma16(d2[m][1], msg, c.oht[2], c.oht[3]);
            }
        };
        {
            int g = 0;
            while (g < ngv && s_cnt[g] == 0) { init_agg(g); finish(g); g++; }
            if (g < ngv) {
                Buf A, B;
                load_ha(g);
                load_gate(A, [] {});
                init_agg(g);
                while (true) {
                    int rem = s_cnt[g] - 16;
                    while (rem > 16) {
                        load_gate(B, [&] { message(A); });
                        load_gate(A, [&] { message(B); });
                        rem -= 32;
                    }
                    if (rem > 0) {
                        load_gate(B, [&] { message(A); });
                        message(B);
                    } else {
                        message(A);
                    }
                    int gn = g + 1;
                    while (gn < ngv && s_cnt[gn] == 0) gn++;
                    if (gn < ngv) {
                        load_ha(gn);
                        load_gate(A, [&] { finish(g); });
                    } else {
                        finish(g);
                    }
                    for (int k = g + 1; k < gn; k++) { init_agg(k); finish(k); }
                    if (gn >= ngv) break;
                    init_agg(gn);
                    g = gn;
                }
            }
        }
    } else {
        const int pw = warp - NCONS;
        if (pw == 0) {
            if (lane == 0) {
                const unsigned target = (ld_acquire(p.barB) / G + 1) * G;
                bool arrived = false;
                int slot = 0, ph = 0;
                for (int i = NWS; i < 32; i++) {
                    mbar_wait(sb + BAR_WE + 8 * slot, ph);
                    load_w(i, slot);
                    if (++slot == NWS) { slot = 0; ph ^= 1; }
                    if (!arrived && mbar_test(sb + BAR_TD, 0)) {
                        asm volatile("red.release.gpu.global.add.u32 [%0], 1;" ::"l"(p.barB) : "memory");
                        arrived = true;
                    }
                }
                if (!arrived) {
                    mbar_wait(sb + BAR_TD, 0);
                    asm volatile("red.release.gpu.global.add.u32 [%0], 1;" ::"l"(p.barB) : "memory");
                }
                grid_wait(p.barB, target);
                mbar_arrive(sb + BAR_GO);
            }
            __syncwarp();
        } else {
            const int t = threadIdx.x - (NCONS + 1) * 32;
            if (t == 0) {
                asm volatile("mbarrier.arrive.relaxed.cluster.shared::cluster.b64 _, [%0];" ::"r"(mapa(sb + BAR_PSF, rank ^ 1)) : "memory");
                const unsigned target = grid_arrive(p.barA);
                grid_wait(p.barA, target);
            }
            bar_sync(4, NB2);
            int* s_g = reinterpret_cast<int*>(smem_raw + SM_CNT);
            bool slow;
            {
                constexpr int NIT = (GMAX + 2 * NW2 - 1) / (2 * NW2);
                const int w3 = pw - 1, slot = lane & 15, hs = (lane >> 4) * 16;
                const int src0 = 2 * w3 + (lane >> 4);
                const int2* box = &p.inbox[(c * G + src0) * PAIR + slot];
                int2 rv[NIT];
#pragma unroll
                for (int i = 0; i < NIT; i++) rv[i] = 2 * NW2 * i + src0 < G ? __ldcg(box + 2 * NW2 * i * PAIR) : make_int2(0, 0);
                uint32_t lo = 0, hi = 0, vmask = 0, big = 0;
                bool over = false;
#pragma unroll
                for (int i = 0; i < NIT; i++) {
                    const uint32_t both = __reduce_add_sync(0xffffffffu, slot == 0 ? (uint32_t)min(rv[i].x, 0xFFFF) << hs : 0u);
                    const int tot = (both >> hs) & 0xFFFF;
                    over |= tot >= PAIR;
                    const bool valid = tot < PAIR && slot >= 1 && slot <= tot;
                    big |= (tot < PAIR && 16 + slot <= tot) ? 1u << i : 0u;
                    vmask |= valid ? 1u << i : 0u;
                    const int g = rv[i].y >> 22;
                    lo += valid && g < 3 ? 1u << (10 * g) : 0u;
                    hi += valid && g >= 3 ? 1u << (10 * (g - 3)) : 0u;
                }
                int2 w0 = make_int2(0, 0);
                if (big) w0 = __ldcg(box + 2 * NW2 * (__ffs(big) - 1) * PAIR + 16);
                uint32_t slo = lo, shi = hi;
#pragma unroll
                for (int d = 1; d < 32; d <<= 1) {
                    const uint32_t u = __shfl_up_sync(0xffffffffu, slo, d), v = __shfl_up_sync(0xffffffffu, shi, d);
                    if (lane >= d) { slo += u; shi += v; }
                }
                uint32_t* s_wt = reinterpret_cast<uint32_t*>(smem_raw + SM_SLOT);
                if (lane == 31) { s_wt[2 * w3] = slo; s_wt[2 * w3 + 1] = shi; }
                if (__any_sync(0xffffffffu, over) && lane == 0) s_g[MAXNG] = 1;
                bar_sync(4, NB2);
                slo -= lo; shi -= hi;
                {
                    int gt = 0;
                    const int sh = t < 3 ? 10 * t : 10 * (t - 3);
#pragma unroll
                    for (int w = 0; w < NW2; w++) {
                        const uint32_t l = s_wt[2 * w], h = s_wt[2 * w + 1];
                        if (w < w3) { slo += l; shi += h; }
                        gt += ((t < 3 ? l : h) >> (sh & 31)) & 1023;
                    }
                    if (t < MAXNG) s_g[t] = gt;
                }
                unsigned* s_roff = reinterpret_cast<unsigned*>(smem_raw + SM_ROFF);
                unsigned* s_rmeta = reinterpret_cast<unsigned*>(smem_raw + SM_RMETA);
#pragma unroll
                for (int i = 0; i < NIT; i++) {
                    const bool valid = (vmask >> i) & 1;
                    const uint32_t r = (uint32_t)rv[i].y >> 18, g = r >> 4;
                    const bool glo = g < 3;
                    const uint32_t sh = 10 * g - (glo ? 0 : 30);
                    const uint32_t pos = ((glo ? slo : shi) >> (sh & 31)) & 1023;
                    const uint32_t inc = valid ? 1u << (sh & 31) : 0u;
                    slo += glo ? inc : 0u;
                    shi += glo ? 0u : inc;
                    const uint32_t a = sb + SM_ROFF + 4 * (g * p.capg + pos);
                    asm volatile("{\n.reg .pred q;\nsetp.ne.u32 q, %3, 0;\n@q st.shared.u32 [%0], %1;\n@q st.shared.u32 [%0 + %4], %2;\n}"
                                 ::"r"(a), "r"((unsigned)rv[i].x * 1024u), "r"((rv[i].y & 0x3FFFF) | ((r & 15) << 18)),
                                   "r"((uint32_t)(valid && pos < (uint32_t)p.capg)), "n"(SM_RMETA - SM_ROFF) : "memory");
                }
                bar_sync(4, NB2);
                bool first = true;
                while (big) {
                    const int i = __ffs(big) - 1;
                    big &= big - 1;
                    const int2 v = first ? w0 : __ldcg(box + 2 * NW2 * i * PAIR + 16);
                    first = false;
                    const int r = v.y >> 18, ps = atomicAdd(&s_g[r >> 4], 1);
                    if (ps < p.capg) {
                        s_roff[(r >> 4) * p.capg + ps] = (unsigned)v.x * 1024u;
                        s_rmeta[(r >> 4) * p.capg + ps] = (v.y & 0x3FFFF) | ((r & 15) << 18);
                    }
                }
                bar_sync(4, NB2);
                slow = s_g[MAXNG] != 0;
                for (int g = 0; g < p.ng; g++) slow |= s_g[g] > p.capg;
            }
            if (slow) {
                bar_sync(4, NB2);
                if (t < MAXNG) s_g[t] = 0;
                if (t == 0) s_g[MAXNG] = 1;
                bar_sync(4, NB2);
                for (int e = t; e < p.E; e += NB2) {
                    const int d = __ldg(p.dst + e);
                    if (d >= n0 && d < n1) atomicAdd(&s_g[(d - n0) >> 4], 1);
                }
            }
            bar_sync(4, NB2);
            if (t == 0) mbar_arrive(sb + BAR_CNT);
        }
        const int gp = pw;
        if (gp >= NPROD) return;
        mbar_wait(sb + BAR_CNT, 0);
        const bool slow = s_cnt[MAXNG] != 0;
        const int ngv = min(p.ng, (n1 - n0 + 15) >> 4);
        if (!slow) {
            uint32_t sw[8];
#pragma unroll
            for (int k = 0; k < 8; k++) sw[k] = (lane >> 3) * 128 + (((lane & 7) ^ k) << 4);
            const char* tb16 = p.tabT + lane * 16;
            int g = 0, j = gp;
            int cn = ngv > 0 ? s_cnt[0] : 0, nch = (cn + 15) >> 4;
            uint32_t stage = gp % NST, phase = (gp / NST) & 1;
            static_assert(4 * STAGEB <= 4 * XKB && STAGEB <= XKB, "ring stage s < 4 lies in the k blocks 0..s of x");
            int it = gp;
            mbar_wait(sb + BAR_GO, 0);
            while (true) {
                while (g < ngv && j >= nch) { j -= nch; g++; cn = g < ngv ? s_cnt[g] : 0; nch = (cn + 15) >> 4; }
                if (g >= ngv) break;
                const uint32_t st = sb + stage * STAGEB, fb = sb + BAR_FULL + 8 * stage;
                if (it < NST) mbar_wait(it < 4 ? sb + BAR_XE + 8 * it : sb + BAR_GD, 0);
                it += NPROD;
                const int slot0 = g * p.capg + 16 * j;
                const int nv = cn - 16 * j;
                if (nv >= 16) {
                    const uint32_t ra = sb + SM_ROFF + 4 * slot0;
                    const uint4 o0 = lds128(ra), o1 = lds128(ra + 16), o2 = lds128(ra + 32), o3 = lds128(ra + 48);
                    uint32_t meta;
                    asm volatile("ld.shared.u32 %0, [%1];" : "=r"(meta) : "r"(sb + SM_RMETA + 4 * (slot0 + (lane >> 1))));
                    const uint32_t of[16] = {o0.x, o0.y, o0.z, o0.w, o1.x, o1.y, o1.z, o1.w,
                                             o2.x, o2.y, o2.z, o2.w, o3.x, o3.y, o3.z, o3.w};
                    mbar_wait(fb + (BAR_EMPTY - BAR_FULL), phase ^ 1);
#pragma unroll
                    for (int k = 0; k < 16; k++) copy_row(st + sw[k & 7] + k * ROWB, tb16 + of[k]);
                    put_meta(p, st, meta, true, lane);
                    chunk_done(fb, lane);
                } else {
                    uint32_t roff = 0, rmeta = 0;
                    if (lane < nv) {
                        roff = *reinterpret_cast<const unsigned*>(smem_raw + SM_ROFF + 4 * (slot0 + lane));
                        rmeta = *reinterpret_cast<const unsigned*>(smem_raw + SM_RMETA + 4 * (slot0 + lane));
                    }
                    mbar_wait(fb + (BAR_EMPTY - BAR_FULL), phase ^ 1);
                    issue_partial_chunk(p, st, fb, roff, rmeta, nv, lane);
                }
                j += NPROD;
                stage += NPROD;
                if (stage >= NST) { stage -= NST; phase ^= 1; }
            }
        } else if (gp == 0) {
            mbar_wait(sb + BAR_GD, 0);
            mbar_wait(sb + BAR_GO, 0);
            volatile int* s_slot = reinterpret_cast<volatile int*>(smem_raw + SM_SLOT);
            int i = 0;
            for (int g = 0; g < ngv; g++) {
                const int gn0 = n0 + 16 * g, gn1 = min(gn0 + 16, n1);
                const int cn = s_cnt[g];
                int cursor = 0;
                for (int j = 0; 16 * j < cn; j++, i++) {
                    const int stage = i % NST;
                    uint32_t roff = 0, rmeta = 0;
                    const int nv = min(16, cn - 16 * j);
                    int filled = 0;
                    while (filled < nv && cursor < p.E) {
                        const int idx = cursor + lane;
                        const int d = idx < p.E ? __ldg(p.dst + idx) : -1;
                        const bool hit = d >= gn0 && d < gn1;
                        const unsigned mm = __ballot_sync(0xffffffffu, hit);
                        const int slot = filled + __popc(mm & ((1u << lane) - 1));
                        const bool take = hit && slot < nv;
                        if (take) s_slot[slot] = idx;
                        const unsigned tk = __ballot_sync(0xffffffffu, take);
                        filled += __popc(tk);
                        cursor = (filled >= nv) ? cursor + (32 - __clz(tk)) : cursor + 32;
                    }
                    __syncwarp();
                    if (lane < nv) {
                        const int e = s_slot[lane];
                        roff = (unsigned)__ldg(p.src + e) * 1024u;
                        rmeta = e | ((__ldg(p.dst + e) - gn0) << 18);
                    }
                    __syncwarp();
                    const uint32_t st = sb + stage * STAGEB, fb = sb + BAR_FULL + 8 * stage;
                    mbar_wait(fb + (BAR_EMPTY - BAR_FULL), ((i / NST) & 1) ^ 1);
                    issue_partial_chunk(p, st, fb, roff, rmeta, nv, lane);
                }
            }
        }
    }
}

__device__ __nv_bfloat16 g_fbS[NPAD_MAX * 512];
__device__ float g_fbAgg[NPAD_MAX * D];

__global__ void __launch_bounds__(256) fb_gemm_kernel(const __nv_bfloat16* __restrict__ x, const __nv_bfloat16* __restrict__ g_w,
                                                      const __nv_bfloat16* __restrict__ v_w, const __nv_bfloat16* __restrict__ u_w, int N) {
    __shared__ float xs[8][D];
    const int r0 = blockIdx.x * 8, j = threadIdx.x;
    for (int r = 0; r < 8; r++) xs[r][j] = r0 + r < N ? __bfloat162float(x[(size_t)(r0 + r) * D + j]) : 0.f;
    __syncthreads();
    for (int m = 0; m < 4; m++) {
        const __nv_bfloat16* w = m == 0 ? g_w : (m == 1 ? g_w + D * D : (m == 2 ? v_w : u_w));
        float acc[8] = {0.f, 0.f, 0.f, 0.f, 0.f, 0.f, 0.f, 0.f};
        for (int k = 0; k < D; k++) {
            const float wv = __bfloat162float(w[k * D + j]);
#pragma unroll
            for (int r = 0; r < 8; r++) acc[r] = fmaf(xs[r][k], wv, acc[r]);
        }
        __nv_bfloat16* dst = (m == 1 || m == 2 ? g_T : g_fbS) + (m >= 2 ? D : 0) + j;
        for (int r = 0; r < 8; r++)
            if (r0 + r < N) dst[(size_t)(r0 + r) * 512] = __float2bfloat16(acc[r]);
    }
    for (int r = 0; r < 8; r++)
        if (r0 + r < N) g_fbAgg[(size_t)(r0 + r) * D + j] = 0.f;
}
__global__ void __launch_bounds__(256) fb_edge_kernel(const __nv_bfloat16* __restrict__ e_attr, const int* __restrict__ src,
                                                      const int* __restrict__ dst, const __nv_bfloat16* __restrict__ cw, int E) {
    __shared__ float cs[DE][D];
    const int j = threadIdx.x;
    for (int k = 0; k < DE; k++) cs[k][j] = __bfloat162float(cw[k * D + j]);
    for (int e = blockIdx.x; e < E; e += gridDim.x) {
        const int s = src[e], d = dst[e];
        float z = __bfloat162float(g_fbS[(size_t)d * 512 + j]) + __bfloat162float(g_T[(size_t)s * 512 + j]);
#pragma unroll
        for (int k = 0; k < DE; k++) z = fmaf(__bfloat162float(e_attr[(size_t)e * DE + k]), cs[k][j], z);
        atomicAdd(&g_fbAgg[(size_t)d * D + j], __bfloat162float(g_T[(size_t)s * 512 + D + j]) / (1.f + __expf(-z)));
    }
}
__global__ void __launch_bounds__(256) fb_out_kernel(__nv_bfloat16* __restrict__ out) {
    const int i = blockIdx.x, j = threadIdx.x;
    const float v = __bfloat162float(g_fbS[(size_t)i * 512 + D + j]) + g_fbAgg[(size_t)i * D + j];
    out[(size_t)i * D + j] = __float2bfloat16(v / (1.f + __expf(-v)));
}

typedef CUresult (*EncodeTiledFn)(CUtensorMap*, CUtensorMapDataType, cuuint32_t, void*, const cuuint64_t*, const cuuint64_t*,
                                  const cuuint32_t*, const cuuint32_t*, CUtensorMapInterleave, CUtensorMapSwizzle,
                                  CUtensorMapL2promotion, CUtensorMapFloatOOBfill);

bool make_map(EncodeTiledFn fn, CUtensorMap* m, const void* ptr, uint64_t rows, uint64_t cols, uint32_t box_rows) {
    cuuint64_t dims[3] = {64, rows, cols / 64};
    cuuint64_t strides[2] = {cols * 2, 128};
    cuuint32_t box[3] = {64, box_rows, 1};
    cuuint32_t estr[3] = {1, 1, 1};
    return fn(m, CU_TENSOR_MAP_DATA_TYPE_BFLOAT16, 3, const_cast<void*>(ptr), dims, strides, box, estr,
              CU_TENSOR_MAP_INTERLEAVE_NONE, CU_TENSOR_MAP_SWIZZLE_128B, CU_TENSOR_MAP_L2_PROMOTION_L2_128B,
              CU_TENSOR_MAP_FLOAT_OOB_FILL_NONE) == CUDA_SUCCESS;
}

}

extern "C" void kernel_launch(void* const* d_in, const int* in_sizes, int n_in, void* d_out, int out_size) {
    const __nv_bfloat16* x = (const __nv_bfloat16*)d_in[0];
    const __nv_bfloat16* e_attr = (const __nv_bfloat16*)d_in[1];
    const int* src = (const int*)d_in[2];
    const int* dst = (const int*)d_in[3];
    const __nv_bfloat16* u_w = (const __nv_bfloat16*)d_in[4];
    const __nv_bfloat16* v_w = (const __nv_bfloat16*)d_in[5];
    const __nv_bfloat16* g_w = (const __nv_bfloat16*)d_in[6];
    const int N = in_sizes[0] / D, E = in_sizes[2];
    if (N <= 0 || N > NPAD_MAX) return;

    static bool init = false;
    static EncodeTiledFn enc = nullptr;
    static int max_ctas = 0;
    static void *tptr = nullptr, *iptr = nullptr, *aptr = nullptr, *bptr = nullptr;
    if (!init) {
        init = true;
        void* fn = nullptr;
        cudaDriverEntryPointQueryResult qr;
        if (cudaGetDriverEntryPoint("cuTensorMapEncodeTiled", &fn, cudaEnableDefault, &qr) == cudaSuccess) enc = (EncodeTiledFn)fn;
        if (cudaFuncSetAttribute(mpnn_fused_kernel, cudaFuncAttributeMaxDynamicSharedMemorySize, SM_ALLOC) == cudaSuccess) {
            cudaLaunchConfig_t cfg = {};
            cfg.gridDim = dim3(GMAX);
            cfg.blockDim = dim3(NTHREADS);
            cfg.dynamicSmemBytes = SM_ALLOC;
            cudaLaunchAttribute at;
            at.id = cudaLaunchAttributeClusterDimension;
            at.val.clusterDim.x = 2; at.val.clusterDim.y = 1; at.val.clusterDim.z = 1;
            cfg.attrs = &at;
            cfg.numAttrs = 1;
            int nc = 0;
            if (cudaOccupancyMaxActiveClusters(&nc, mpnn_fused_kernel, &cfg) == cudaSuccess) max_ctas = 2 * nc;
        }
        cudaGetSymbolAddress(&tptr, g_T);
        cudaGetSymbolAddress(&iptr, g_inbox);
        cudaGetSymbolAddress(&aptr, g_barA);
        cudaGetSymbolAddress(&bptr, g_barB);
        (void)cudaGetLastError();
    }

    const int G = GMAX;
    Params p;
    p.e_attr = e_attr; p.src = src; p.dst = dst; p.cw = g_w + 512 * D; p.out = (__nv_bfloat16*)d_out;
    p.tabT = (const char*)tptr;
    p.inbox = (int2*)iptr; p.barA = (unsigned*)aptr; p.barB = (unsigned*)bptr;
    p.wG = (const char*)g_w; p.wV = (const char*)v_w; p.wU = (const char*)u_w;
    p.N = N; p.E = E;
    p.npc = (N + G - 1) / G; p.ng = (p.npc + 15) / 16; p.epc = (E + G - 1) / G;
    p.magic = (unsigned)((0x100000000ull + p.npc - 1) / p.npc);
    p.capg = min((REC_SLOTS / p.ng) & ~15, 1008);
    const int trows = (G / 2 - 1) * 2 * p.npc + NPAIR;
    bool fast = enc && max_ctas >= G && p.npc <= NPC_MAX && p.npc >= 16 && p.epc <= NBIN * EPT && trows <= NPAD_MAX && E <= (1 << 18);
    CUtensorMap tmX, tmG, tmV, tmU, tmT;
    fast = fast && make_map(enc, &tmX, x, N, D, NPAIR) && make_map(enc, &tmG, g_w, 2 * D + DE, D, 64) &&
           make_map(enc, &tmV, v_w, D, D, 64) && make_map(enc, &tmU, u_w, D, D, 64) && make_map(enc, &tmT, tptr, trows, 512, NPAIR);
    if (fast) {
        mpnn_fused_kernel<<<G, NTHREADS, SM_ALLOC>>>(tmX, tmG, tmV, tmU, tmT, p);
    } else {
        fb_gemm_kernel<<<(N + 7) / 8, 256>>>(x, g_w, v_w, u_w, N);
        if (E > 0) fb_edge_kernel<<<min(E, 4096), 256>>>(e_attr, src, dst, p.cw, E);
        fb_out_kernel<<<N, 256>>>((__nv_bfloat16*)d_out);
    }
}
```
